```python
import torch

def _softmax(x, axis=-1):
    return torch.softmax(x, dim=axis)
def _gelu(x):
    return torch.nn.functional.gelu(x, approximate="tanh")
def _silu(x):
    return torch.nn.functional.silu(x)
def _sigmoid(x):
    return torch.sigmoid(x)
def _layernorm(x, axis=-1, eps=1e-5):
    m = x.mean(dim=axis, keepdim=True)
    v = x.var(dim=axis, keepdim=True, unbiased=False)
    return (x - m) / torch.sqrt(v + eps)
def _scatter_add(tgt, idx, src, axis=0):
    return tgt.clone().index_add_(axis, idx, src)
def _segment_sum(src, seg, n):
    out = torch.zeros((n,) + src.shape[1:], dtype=src.dtype)
    return out.index_add_(0, seg, src)
def _pad(x, pw):
    flat = tuple(v for pair in reversed(pw) for v in pair)
    return torch.nn.functional.pad(x, flat)

kernel_name = 'parallel_sum__spectral_fnet__moe_arch_mod__prompt'

def setup_inputs():

    _w = (lambda a: (lambda t: t.to(torch.bfloat16) if t.is_floating_point() else t)(torch.as_tensor(a)))
    def _A_setup():
        B, S, D = 1, 2048, 1024
        ns = torch.arange(S)[:, None] * torch.arange(S)[None, :]
        nd = torch.arange(D)[:, None] * torch.arange(D)[None, :]
        Ws_re = torch.cos(-2.0 * torch.pi * ns / S).to(float)
        Ws_im = torch.sin(-2.0 * torch.pi * ns / S).to(float)
        Wd_re = torch.cos(-2.0 * torch.pi * nd / D).to(float)
        Wd_im = torch.sin(-2.0 * torch.pi * nd / D).to(float)
        return {
            "x": _w((lambda *s: torch.randn(*s, dtype=torch.bfloat16) * 0.05)(B, S, D)),
            "dft_seq_re": _w(Ws_re),
            "dft_seq_im": _w(Ws_im),
            "dft_hid_re": _w(Wd_re),
            "dft_hid_im": _w(Wd_im),
        }
    _A_in = _A_setup()

    def _B_setup():
        B, S, D, F, C = 1, 2048, 1024, 3584, 2
        return {
            "x": _w((lambda *s: torch.randn(*s, dtype=torch.bfloat16) * 0.05)(B, S, D)),
            "w_r": _w((lambda *s: torch.randn(*s, dtype=torch.bfloat16) * 1.6)(D)),
            "w_gate": _w((lambda *s: torch.randn(*s, dtype=torch.bfloat16) * 0.4)(D, F)),
            "w_up": _w((lambda *s: torch.randn(*s, dtype=torch.bfloat16) * 0.4)(D, F)),
            "w_down": _w((lambda *s: torch.randn(*s, dtype=torch.bfloat16) * 0.4)(F, D)),
        }
    _B_in = _B_setup()

    return {
        "A_x": _A_in["x"],
        "A_dft_seq_re": _A_in["dft_seq_re"],
        "A_dft_seq_im": _A_in["dft_seq_im"],
        "A_dft_hid_re": _A_in["dft_hid_re"],
        "A_dft_hid_im": _A_in["dft_hid_im"],
        "B_x": _B_in["x"],
        "B_w_r": _B_in["w_r"],
        "B_w_gate": _B_in["w_gate"],
        "B_w_up": _B_in["w_up"],
        "B_w_down": _B_in["w_down"],
    }

def reference(A_x, A_dft_seq_re, A_dft_seq_im, A_dft_hid_re, A_dft_hid_im, B_x, B_w_r, B_w_gate, B_w_up, B_w_down):
    def _A_ref(x, dft_seq_re, dft_seq_im, dft_hid_re, dft_hid_im):
        a = torch.einsum("bsd,ed->bse", x, dft_hid_re)
        b = torch.einsum("bsd,ed->bse", x, dft_hid_im)
        y = torch.einsum("ts,bse->bte", dft_seq_re, a) - torch.einsum("ts,bse->bte", dft_seq_im, b)
        return y

    def _B_ref(x, w_r, w_gate, w_up, w_down):
        B, S, D = x.shape
        C = 2
        r = x @ w_r
        idx = torch.argsort(-r, axis=-1)[:, :C]
        idx_e = (lambda x, n, axis: torch.repeat_interleave(x, n, dim=axis))(idx.reshape(B, C, 1), D, axis=2)
        x_sel = (lambda x, i, axis: torch.take_along_dim(x, i, dim=axis))(x, idx_e, axis=1)
        g = _silu(x_sel @ w_gate)
        u = x_sel @ w_up
        y = (g * u) @ w_down
        r_sel = _sigmoid((lambda x, i, axis: torch.take_along_dim(x, i, dim=axis))(r, idx, axis=1))
        y = y * r_sel.reshape(B, C, 1)
        b_off = (torch.arange(B) * S).reshape(B, 1)
        flat_idx = (idx + b_off).reshape(B * C)
        zero = (x * 0.0).reshape(B * S, D)
        upd = _scatter_add(zero, flat_idx, y.reshape(B * C, D), axis=0)
        return x + upd.reshape(B, S, D)

    x = A_x
    xn = _layernorm(x, axis=-1)
    return x + _A_ref(xn, A_dft_seq_re, A_dft_seq_im, A_dft_hid_re, A_dft_hid_im) + _B_ref(xn, B_w_r, B_w_gate, B_w_up, B_w_down)
```

```cpp
#include <cuda_runtime.h>
#include <cuda_bf16.h>
#include <cuda.h>
#include <stdint.h>

#define DEVI __device__ __forceinline__

namespace {

constexpr int S_ = 2048, D_ = 1024, F_ = 3584;
constexpr int STAGES = 4;
constexpr int A_BYTES = 128 * 64 * 2, B_BYTES = 256 * 64 * 2;
constexpr int K1 = 16, K2 = 32, KT = K1 + K2;
constexpr int NCTA = 128;
constexpr int NFFN = 112;
constexpr int CP0 = 2;
constexpr int LEAD2 = 4;
constexpr int OMASK = 11;
#define PG 4
constexpr int PR = 64 / PG;
constexpr int NMIR = 4;
constexpr int LN_K0 = 4;
constexpr int GU_KF = 15;
constexpr int GU_K0 = 24;
constexpr int H_K = 36;
constexpr unsigned long long WS_MASK = 0x55540b6e80ull;

constexpr int OFF_B = STAGES * A_BYTES;
constexpr int OFF_AUX = OFF_B + STAGES * B_BYTES;
constexpr int OFF_RING = 0;
constexpr int OFF_XS = OFF_RING + 3 * 8192;
constexpr int OFF_GU = OFF_XS + 4096;
constexpr int OFF_MEAN = OFF_GU;
constexpr int OFF_COLSTAT = OFF_XS + 8192;
constexpr int OFF_RED = OFF_COLSTAT;
constexpr int OFF_WSUM = OFF_COLSTAT + 512;
constexpr int OFF_FLAGS = OFF_COLSTAT + 1536;
constexpr int OFF_BAR = OFF_COLSTAT + 2048;
constexpr int OFF_MISC = OFF_BAR + 224;
constexpr int AUX_BYTES = OFF_MISC + 32;
constexpr int SMEM_BYTES = OFF_AUX + AUX_BYTES;
static_assert(SMEM_BYTES <= 232448, "smem");

template <int V> struct IC { static constexpr int value = V; };

struct Maps {
  CUtensorMap x, wd[2], ws[2], ws_pf[2], ab_ld, ab_st, out;
};

__device__ __nv_bfloat16 g_ab[2 * D_ * S_];
__device__ uint2 g_stat[S_];
__device__ uint2 g_wsum[2 * D_];
__device__ uint2 g_cand[NCTA * 3];
__device__ uint2 g_h[F_];
__device__ uint2 g_yp[NCTA * 128];
__device__ __align__(128) uint32_t g_abflag[16 * 3 * 32];
__device__ uint32_t g_ctr;
#define TL(i) do {} while (0)
#define TK(r, k) do {} while (0)

DEVI uint32_t smem_u32(const void* p) { return (uint32_t)__cvta_generic_to_shared(p); }
DEVI void mbar_init(uint32_t bar, uint32_t cnt) { asm volatile("mbarrier.init.shared::cta.b64 [%0], %1;" ::"r"(bar), "r"(cnt) : "memory"); }
DEVI void mbar_expect_tx(uint32_t bar, uint32_t bytes) { asm volatile("mbarrier.arrive.expect_tx.shared::cta.b64 _, [%0], %1;" ::"r"(bar), "r"(bytes) : "memory"); }
DEVI void mbar_arrive(uint32_t bar) { asm volatile("mbarrier.arrive.shared::cta.b64 _, [%0];" ::"r"(bar) : "memory"); }
DEVI void mbar_arrive_cluster(uint32_t bar, uint32_t cta) {
  asm volatile("{\n.reg .b32 ra;\nmapa.shared::cluster.u32 ra, %0, %1;\nmbarrier.arrive.shared::cluster.b64 _, [ra];\n}" ::"r"(bar), "r"(cta) : "memory");
}
DEVI uint32_t mapa(uint32_t a, uint32_t cta) { uint32_t r; asm("mapa.shared::cluster.u32 %0, %1, %2;" : "=r"(r) : "r"(a), "r"(cta)); return r; }
DEVI void st_async4(uint32_t dst, float a, float b, float c, float d, uint32_t bar) {
  asm volatile("st.async.shared::cluster.mbarrier::complete_tx::bytes.v4.f32 [%0], {%1, %2, %3, %4}, [%5];"
               ::"r"(dst), "f"(a), "f"(b), "f"(c), "f"(d), "r"(bar) : "memory");
}
DEVI bool mbar_try_wait(uint32_t bar, uint32_t parity) {
  uint32_t ok;
  asm volatile("{\n.reg .pred p;\nmbarrier.try_wait.parity.shared::cta.b64 p, [%1], %2;\nselp.u32 %0, 1, 0, p;\n}" : "=r"(ok) : "r"(bar), "r"(parity) : "memory");
  return ok;
}
DEVI bool mbar_test(uint32_t bar, uint32_t parity) {
  uint32_t ok;
  asm volatile("{\n.reg .pred p;\nmbarrier.test_wait.parity.shared::cta.b64 p, [%1], %2;\nselp.u32 %0, 1, 0, p;\n}" : "=r"(ok) : "r"(bar), "r"(parity) : "memory");
  return ok;
}
DEVI void mbar_wait(uint32_t bar, uint32_t parity) {
  uint32_t n = 0;
  while (!mbar_try_wait(bar, parity)) { if (++n > (1u << 20)) __trap(); }
}
DEVI uint64_t policy_evict_first() {
  uint64_t p;
  asm volatile("createpolicy.fractional.L2::evict_first.b64 %0, 1.0;" : "=l"(p));
  return p;
}
DEVI void tma_load(uint32_t dst, const CUtensorMap* m, int c0, int c1, uint32_t bar) {
  asm volatile("cp.async.bulk.tensor.2d.shared::cluster.global.mbarrier::complete_tx::bytes [%0], [%1, {%3, %4}], [%2];"
               ::"r"(dst), "l"(m), "r"(bar), "r"(c0), "r"(c1) : "memory");
}
DEVI void tma_load5(uint32_t dst, const CUtensorMap* m, int c0, int c4, uint32_t bar) {
  asm volatile("cp.async.bulk.tensor.5d.shared::cluster.global.mbarrier::complete_tx::bytes [%0], [%1, {%3, %5, %5, %5, %4}], [%2];"
               ::"r"(dst), "l"(m), "r"(bar), "r"(c0), "r"(c4), "r"(0) : "memory");
}
DEVI void tma_store(const CUtensorMap* m, uint32_t src, int c0, int c1) {
  asm volatile("cp.async.bulk.tensor.2d.global.shared::cta.bulk_group [%0, {%2, %3}], [%1];" ::"l"(m), "r"(src), "r"(c0), "r"(c1) : "memory");
}
DEVI void tma_red_add(const CUtensorMap* m, uint32_t src, int c0, int c1) {
  asm volatile("cp.reduce.async.bulk.tensor.5d.global.shared::cta.add.bulk_group [%0, {%2, %4, %4, %4, %3}], [%1];" ::"l"(m), "r"(src), "r"(c0), "r"(c1), "r"(0) : "memory");
}
DEVI uint4 lds128(uint32_t a) { uint4 v; asm volatile("ld.shared.v4.u32 {%0,%1,%2,%3}, [%4];" : "=r"(v.x), "=r"(v.y), "=r"(v.z), "=r"(v.w) : "r"(a) : "memory"); return v; }
DEVI uint32_t lds32(uint32_t a) { uint32_t v; asm volatile("ld.volatile.shared.u32 %0, [%1];" : "=r"(v) : "r"(a) : "memory"); return v; }
DEVI void sts32(uint32_t a, uint32_t v) { asm volatile("st.volatile.shared.u32 [%0], %1;" ::"r"(a), "r"(v) : "memory"); }
DEVI void tma_prefetch(const CUtensorMap* m, int c0, int c1) {
  asm volatile("cp.async.bulk.prefetch.tensor.5d.L2.global [%0, {%1, %3, %3, %3, %2}];" ::"l"(m), "r"(c0), "r"(c1), "r"(0) : "memory");
}
DEVI void cp_async16(uint32_t dst, const void* src) { asm volatile("cp.async.cg.shared.global [%0], [%1], 16;" ::"r"(dst), "l"(src) : "memory"); }
DEVI void cp_async16_hint(uint32_t dst, const void* src, uint64_t pol) {
  asm volatile("cp.async.cg.shared.global.L2::cache_hint [%0], [%1], 16, %2;" ::"r"(dst), "l"(src), "l"(pol) : "memory");
}
DEVI bool elect_one() {
  uint32_t p;
  asm volatile("{\n.reg .pred P;\nelect.sync _|P, 0xffffffff;\nselp.u32 %0, 1, 0, P;\n}" : "=r"(p));
  return p;
}
DEVI float sqrt_approx(float v) { float r; asm("sqrt.approx.ftz.f32 %0, %1;" : "=f"(r) : "f"(v)); return r; }
DEVI float rcp_approx(float v) { float r; asm("rcp.approx.ftz.f32 %0, %1;" : "=f"(r) : "f"(v)); return r; }
DEVI void bulk_commit() { asm volatile("cp.async.bulk.commit_group;" ::: "memory"); }
template <int N> DEVI void bulk_wait() { asm volatile("cp.async.bulk.wait_group %0;" ::"n"(N) : "memory"); }
template <int N> DEVI void bulk_wait_read() { asm volatile("cp.async.bulk.wait_group.read %0;" ::"n"(N) : "memory"); }
DEVI void fence_proxy_async() { asm volatile("fence.proxy.async.global;" ::: "memory"); }
DEVI void fence_proxy_async_smem() { asm volatile("fence.proxy.async.shared::cta;" ::: "memory"); }
DEVI void prefetch_map(const CUtensorMap* m) { asm volatile("prefetch.tensormap [%0];" ::"l"(m) : "memory"); }
DEVI void named_bar(int id, int n) { asm volatile("bar.sync %0, %1;" ::"r"(id), "r"(n) : "memory"); }
DEVI void named_arrive(int id, int n) { asm volatile("bar.arrive %0, %1;" ::"r"(id), "r"(n) : "memory"); }
DEVI void wgmma_fence() { asm volatile("wgmma.fence.sync.aligned;" ::: "memory"); }
DEVI void wgmma_commit() { asm volatile("wgmma.commit_group.sync.aligned;" ::: "memory"); }
template <int N> DEVI void wgmma_wait() { asm volatile("wgmma.wait_group.sync.aligned %0;" ::"n"(N) : "memory"); }
DEVI uint64_t make_desc(uint32_t addr) {
  return (uint64_t)((addr & 0x3FFFF) >> 4) | ((uint64_t)1 << 16) | ((uint64_t)64 << 32) | ((uint64_t)1 << 62);
}
DEVI uint32_t ld_acquire(const uint32_t* p) { uint32_t v; asm volatile("ld.acquire.gpu.global.u32 %0, [%1];" : "=r"(v) : "l"(p) : "memory"); return v; }
DEVI void fence_gpu() { asm volatile("fence.acq_rel.gpu;" ::: "memory"); }
DEVI uint32_t ld_relaxed(const uint32_t* p) { uint32_t v; asm volatile("ld.relaxed.gpu.global.u32 %0, [%1];" : "=r"(v) : "l"(p) : "memory"); return v; }
DEVI void st_rec(uint2* p, uint32_t a, uint32_t b) {
  asm volatile("{\n.reg .b64 t;\nmov.b64 t, {%1, %2};\nst.relaxed.gpu.global.b64 [%0], t;\n}" ::"l"(p), "r"(a), "r"(b) : "memory");
}
DEVI uint4 ld_rec2(const uint2* p) {
  uint4 v;
  asm volatile("{\n.reg .b64 a, b;\nld.relaxed.gpu.global.v2.b64 {a, b}, [%4];\nmov.b64 {%0, %1}, a;\nmov.b64 {%2, %3}, b;\n}"
               : "=r"(v.x), "=r"(v.y), "=r"(v.z), "=r"(v.w) : "l"(p) : "memory");
  return v;
}
DEVI uint2 ld_rec(const uint2* p) {
  uint2 v;
  asm volatile("{\n.reg .b64 a;\nld.relaxed.gpu.global.b64 a, [%2];\nmov.b64 {%0, %1}, a;\n}" : "=r"(v.x), "=r"(v.y) : "l"(p) : "memory");
  return v;
}
DEVI bool poll_again(bool bad, uint32_t& it) {
  if (!__any_sync(0xffffffffu, bad)) return false;
  if (++it > (1u << 18)) __trap();
  __nanosleep(40);
  return true;
}
DEVI void st_relaxed(uint32_t* p, uint32_t v) { asm volatile("st.relaxed.gpu.global.u32 [%0], %1;" ::"l"(p), "r"(v) : "memory"); }
DEVI uint32_t pack_bf16(float lo, float hi) { uint32_t r; asm("cvt.rn.bf16x2.f32 %0, %1, %2;" : "=r"(r) : "f"(hi), "f"(lo)); return r; }
DEVI float bf_lo(uint32_t v) { return __uint_as_float(v << 16); }
DEVI float bf_hi(uint32_t v) { return __uint_as_float(v & 0xffff0000u); }
DEVI float bf_round(float v) { return bf_hi(pack_bf16(0.f, v)); }
DEVI uint32_t bf2_sub(uint32_t a, uint32_t b) { uint32_t r; asm("sub.rn.bf16x2 %0, %1, %2;" : "=r"(r) : "r"(a), "r"(b)); return r; }
DEVI uint32_t bf2_fma(uint32_t a, uint32_t b, uint32_t c) { uint32_t r; asm("fma.rn.bf16x2 %0, %1, %2, %3;" : "=r"(r) : "r"(a), "r"(b), "r"(c)); return r; }
DEVI void prefetch_l2(const void* p, uint32_t bytes) { asm volatile("cp.async.bulk.prefetch.L2.global [%0], %1;" ::"l"(p), "r"(bytes) : "memory"); }
DEVI void stmatrix_x4(uint32_t addr, uint32_t a, uint32_t b, uint32_t c, uint32_t d) {
  asm volatile("stmatrix.sync.aligned.m8n8.x4.shared.b16 [%0], {%1,%2,%3,%4};" ::"r"(addr), "r"(a), "r"(b), "r"(c), "r"(d) : "memory");
}
DEVI void stmatrix_x4_t(uint32_t addr, uint32_t a, uint32_t b, uint32_t c, uint32_t d) {
  asm volatile("stmatrix.sync.aligned.m8n8.x4.trans.shared.b16 [%0], {%1,%2,%3,%4};" ::"r"(addr), "r"(a), "r"(b), "r"(c), "r"(d) : "memory");
}
DEVI void gemv8(float (&acc)[16], const uint4& v, const float2 xv) {
  const uint32_t g4[4] = {v.x, v.y, v.z, v.w};
#pragma unroll
  for (int c = 0; c < 4; c++) {
    const float lo = bf_lo(g4[c]), hi = bf_hi(g4[c]);
    acc[4 * c + 0] = fmaf(lo, xv.x, acc[4 * c + 0]);
    acc[4 * c + 1] = fmaf(lo, xv.y, acc[4 * c + 1]);
    acc[4 * c + 2] = fmaf(hi, xv.x, acc[4 * c + 2]);
    acc[4 * c + 3] = fmaf(hi, xv.y, acc[4 * c + 3]);
  }
}
template <int H, int MASK, int N> DEVI void xreduce(float (&s)[N], int lane) {
  const bool up = lane & MASK;
#pragma unroll
  for (int i = 0; i < H; i++) {
    const float keep = up ? s[i + H] : s[i], send = up ? s[i] : s[i + H];
    s[i] = keep + __shfl_xor_sync(0xffffffffu, send, MASK);
  }
}
DEVI float warp_sum(float v) {
#pragma unroll
  for (int o = 16; o; o >>= 1) v += __shfl_xor_sync(0xffffffffu, v, o);
  return v;
}

#define ACC128 \
      "{%0,%1,%2,%3,%4,%5,%6,%7,%8,%9,%10,%11,%12,%13,%14,%15,%16,%17,%18,%19,%20,%21,%22,%23,%24,%25,%26,%27,%28,%29,%30,%31," \
      "%32,%33,%34,%35,%36,%37,%38,%39,%40,%41,%42,%43,%44,%45,%46,%47,%48,%49,%50,%51,%52,%53,%54,%55,%56,%57,%58,%59,%60,%61,%62,%63," \
      "%64,%65,%66,%67,%68,%69,%70,%71,%72,%73,%74,%75,%76,%77,%78,%79,%80,%81,%82,%83,%84,%85,%86,%87,%88,%89,%90,%91,%92,%93,%94,%95," \
      "%96,%97,%98,%99,%100,%101,%102,%103,%104,%105,%106,%107,%108,%109,%110,%111,%112,%113,%114,%115,%116,%117,%118,%119,%120,%121,%122,%123,%124,%125,%126,%127},"
#define R128(d) R8(d, 0), R8(d, 8), R8(d, 16), R8(d, 24), R8(d, 32), R8(d, 40), R8(d, 48), R8(d, 56), R8(d, 64), R8(d, 72), R8(d, 80), \
                R8(d, 88), R8(d, 96), R8(d, 104), R8(d, 112), R8(d, 120)
#define R8(d, i) "+f"(d[i]), "+f"(d[i + 1]), "+f"(d[i + 2]), "+f"(d[i + 3]), "+f"(d[i + 4]), "+f"(d[i + 5]), "+f"(d[i + 6]), "+f"(d[i + 7])
DEVI void wgmma_n256(float (&d)[128], uint64_t da, uint64_t db, int scale_d) {
  asm volatile("{\n.reg .pred p;\nsetp.ne.b32 p, %130, 0;\nwgmma.mma_async.sync.aligned.m64n256k16.f32.bf16.bf16 " ACC128
               " %128, %129, p, 1, 1, 0, 0;\n}\n" : R128(d) : "l"(da), "l"(db), "r"(scale_d));
}
DEVI void wgmma_n256_rs(float (&d)[128], uint32_t a0, uint32_t a1, uint32_t a2, uint32_t a3, uint64_t db) {
  asm volatile("wgmma.mma_async.sync.aligned.m64n256k16.f32.bf16.bf16 " ACC128 " {%128, %129, %130, %131}, %132, 1, 1, 1, 0;\n"
               : R128(d) : "r"(a0), "r"(a1), "r"(a2), "r"(a3), "l"(db));
}

DEVI void wait_out_init(uint32_t tag) {
  uint32_t it = 0;
  while ((int32_t)(ld_acquire(&g_ctr) - tag) < 0) { if (++it > (1u << 20)) __trap(); }
}
template <int N> DEVI void cp_wait() { asm volatile("cp.async.wait_group %0;" ::"n"(N) : "memory"); }

DEVI int other_chunk(int m, int j) { return m + (m >= j); }
DEVI int p2_col(int n, int j) {
  const int m = n < 11 ? n - 4 : n < 18 ? n - 11 : (n - 18) >> 1;
  const int slab = n < 11 ? 0 : n < 18 ? 1 : 2 + (n & 1);
  return other_chunk(m, j) * 256 + slab * 64;
}

__global__ void __cluster_dims__(2, 1, 1) __launch_bounds__(384, 1)
fused_kernel(const __nv_bfloat16* __restrict__ x, const __nv_bfloat16* __restrict__ wd_re, const __nv_bfloat16* __restrict__ wd_im,
             const __nv_bfloat16* __restrict__ w_r, const __nv_bfloat16* __restrict__ w_gate, const __nv_bfloat16* __restrict__ w_up,
             const __grid_constant__ Maps maps, const __nv_bfloat16* __restrict__ w_down, __nv_bfloat16* __restrict__ out) {
  extern __shared__ __align__(1024) uint8_t smem[];
  const uint32_t base = smem_u32(smem);
  uint8_t* aux = smem + OFF_AUX;
  const uint32_t auxs = base + OFF_AUX;
  const uint32_t full0 = auxs + OFF_BAR, empty0 = full0 + 8 * STAGES, bar_stat = empty0 + 8 * STAGES, bar_ab = bar_stat + 8,
                 bar_out = bar_ab + 32, bar_pub = bar_out + 64, bar_gu = bar_pub + 16;
  const uint32_t kcur = auxs + OFF_MISC + 16;

  const int tid = threadIdx.x, lane = tid & 31;
  const int warp = __shfl_sync(0xffffffffu, tid >> 5, 0);
  const int cl = blockIdx.x >> 1;
  const int pos = cl - 4 + max(((cl - 29) * 37) >> 8, 0) + ((cl - 4) >> 31 & (7 * cl + 36));
  const int bid = ((~pos & 3) * 2 + (pos >> 5)) * 16 + (pos & 4) * 2 + (((pos >> 3) + (pos >> 5)) & 3) * 2 + (blockIdx.x & 1);
  const int eb = bid & 7, part = (bid >> 3) & 1, j = bid >> 4;
  const uint32_t rank = blockIdx.x & 1;
  const __nv_bfloat16* wd_rows = (bid < 64 ? wd_re : wd_im) + (size_t)(bid & 63) * 16 * D_;

  if (tid < 256) {
    const uint32_t dst = base + (tid >> 3) * 128 + (((tid ^ (tid >> 3)) & 7) << 4);
    const __nv_bfloat16* pa = (part ? wd_im : wd_re) + (size_t)(eb * 128 + (tid >> 3)) * D_ + (tid & 7) * 8;
    const __nv_bfloat16* pb = x + (size_t)(j * 256 + (tid >> 3)) * D_ + (tid & 7) * 8;
#pragma unroll
    for (int k = 0; k < CP0; k++) {
      if (k) named_bar(4, 256);
#pragma unroll
      for (int q = 0; q < 12; q++) {
        const uint32_t d = dst + (q < 4 ? k * A_BYTES + q * 4096 : OFF_B + k * B_BYTES + (q - 4) * 4096);
        const __nv_bfloat16* p = (q < 4 ? pa + q * 32 * D_ : pb + (q - 4) * 32 * D_) + k * 64;
        cp_async16(d, p);
      }
      asm volatile("cp.async.commit_group;" ::: "memory");
    }
  }
  if (warp == 9) ((uint4*)(aux + OFF_FLAGS))[lane] = make_uint4(0, 0, 0, 0);
  if (tid == 256) {
    TL(7);
    prefetch_map(&maps.x);
    prefetch_map(&maps.wd[part]);
    if (base & 1023) __trap();
#pragma unroll
    for (int s = 0; s < STAGES; s++) { mbar_init(full0 + 8 * s, 1); mbar_init(empty0 + 8 * s, 2); }
    mbar_init(bar_stat, 1);
#pragma unroll
    for (int s = 0; s < 4; s++) mbar_init(bar_ab + 8 * s, 4);
    mbar_init(bar_pub, 1);
    mbar_init(bar_pub + 8, 2);
    mbar_init(bar_gu, 1);
    mbar_init(bar_pub + 24, 1);
    sts32(kcur, 0);
#pragma unroll
    for (int s = 0; s < 8; s++) mbar_init(bar_out + 8 * s, 4);
    asm volatile("fence.mbarrier_init.release.cluster;" ::: "memory");
  }
  __syncthreads();
  asm volatile("barrier.cluster.arrive.relaxed.aligned;" ::: "memory");
  asm volatile("barrier.cluster.wait.acquire.aligned;" ::: "memory");

  if (warp == 8) {
    if (elect_one()) {
      const int arow = eb * 128;
      int pf_i = 0;
      auto prefetch_ws = [&](int k) {
        if ((WS_MASK >> k) & 1) {
          tma_prefetch(&maps.ws_pf[part], pf_i < 2 ? j * 256 + pf_i * 128 : pf_i < 9 ? other_chunk(pf_i - 2, j) * 256 : other_chunk(pf_i - 9, j) * 256 + 128,
                       (j * 8 + eb) * (PR / 8));
          pf_i++;
        }
      };
      auto load_b = [&](int st, const CUtensorMap* m, int col) { tma_load5(base + OFF_B + st * B_BYTES, m, col, j * PR, full0 + 8 * st); };
      TL(1);
#pragma unroll 1
      for (int k = CP0; k < K1 + 3; k++) {
        const int st = k & 3;
        mbar_wait(empty0 + 8 * st, ((k >> 2) & 1) ^ 1);
        TK(2, k);
        if (k < K1) {
          mbar_expect_tx(full0 + 8 * st, A_BYTES + B_BYTES);
          tma_load(base + OFF_B + st * B_BYTES, &maps.x, k * 64, j * 256, full0 + 8 * st);
          tma_load(base + st * A_BYTES, &maps.wd[part], k * 64, arow, full0 + 8 * st);
        } else {
          mbar_expect_tx(full0 + 8 * st, B_BYTES);
          load_b(st, &maps.ws[part], j * 256 + (k - K1) * 64);
        }
        sts32(kcur, k);
        if (k == 4) { prefetch_map(&maps.ws[part]); prefetch_map(&maps.ws_pf[part]); prefetch_map(&maps.ab_ld); prefetch_map(&maps.ab_st); prefetch_map(&maps.out); }
        prefetch_ws(k);
      }
      mbar_wait(bar_stat, 0);
      const uint32_t tag = lds32(auxs + OFF_MISC);
      uint32_t* flags = g_abflag + (eb * 2 + part) * 96;
      mbar_wait(empty0 + 24, 1);
      sts32(kcur, K1 + 3);
      auto put = [&](int h) {
        tma_store(&maps.ab_st, base + h * (A_BYTES / 2), j * 256 + (h >> 1) * 64, part * 1024 + arow + (h & 1) * 64);
        bulk_commit();
      };
#pragma unroll
      for (int w = 1; w >= 0; w--) {
        mbar_wait(bar_ab + 16 * w, 0);
        put(w);
      }
      TL(8);
      TK(2, K1 + 3);
      mbar_expect_tx(full0 + 24, B_BYTES);
      load_b(3, &maps.ws[part], j * 256 + 192);
      prefetch_ws(K1 + 3);
      bulk_wait<0>();
      TL(11);
      mbar_arrive(bar_pub + 24);
      const uint32_t mirror = auxs + OFF_FLAGS;
      uint32_t mc = 0;
      auto refresh = [&](int col) {
        const int lv = min((col >> 6) & 3, 2);
        cp_async16(mirror + mc + lv * 32, flags + lv * 32);
        cp_async16(mirror + mc + lv * 32 + 16, flags + lv * 32 + 4);
        mc = (mc + 128) & (NMIR * 128 - 1);
      };
      auto ready = [&](int col) {
        const uint32_t a = mirror + min((col >> 6) & 3, 2) * 32 + (col >> 8) * 4;
        uint32_t v[NMIR];
#pragma unroll
        for (int i = 0; i < NMIR; i++) v[i] = lds32(a + i * 128);
        bool r = false;
#pragma unroll
        for (int i = 0; i < NMIR; i++) r |= v[i] == tag;
        return r;
      };
      mbar_wait(bar_ab + 8, 0);
      mbar_wait(bar_ab + 24, 0);
      fence_proxy_async_smem();
      refresh(0);
      {
        uint32_t it = 0;
        while (!mbar_test(empty0, 0)) {
          __nanosleep(150);
          refresh(0);
          if (++it > (1u << 20)) __trap();
        }
      }
#pragma unroll 1
      for (int n = 4; n < K2; n++) {
        const int k = K1 + n, st = k & 3;
        const int col = p2_col(n, j);
        mbar_wait(empty0 + 8 * st, ((k >> 2) & 1) ^ 1);
        TK(2, k);
        mbar_expect_tx(full0 + 8 * st, A_BYTES + B_BYTES);
        load_b(st, &maps.ws[part], col);
        if (n == 4) put(4);
        uint32_t it = 3;
        while (!ready(col)) {
          if ((++it & 3) == 0) refresh(col);
          if (it > (1u << 22)) __trap();
          __nanosleep(32);
        }
        if (n == 5) mbar_wait(bar_pub, 0);
        if (n == 6) bulk_wait_read<1>();
        if (n == 7) { bulk_wait<0>(); mbar_arrive(bar_pub + 8); TL(23); }
        TK(3, k);
        tma_load(base + st * A_BYTES, &maps.ab_ld, col, part * 1024 + arow, full0 + 8 * st);
        if (n < 7) put(n + 1);
        sts32(kcur, k);
        const int col2 = p2_col(min(n + 2, K2 - 1), j);
        if (!ready(col2)) refresh(col2);
        prefetch_ws(k);
      }
      wait_out_init(tag);
      fence_proxy_async();
#pragma unroll 1
      for (int q = 0; q < 8; q++) {
        if (((2 * OMASK + 1) >> (q & 3)) & 1) mbar_wait(bar_out + 8 * ((q & 4) + __ffs(OMASK >> (q & 3)) - 1 + (q & 3)), 0);
        if ((q & 3) == 0) TL(24 + (q >> 2));
        tma_red_add(&maps.out, base + (q & 3) * A_BYTES + (q >> 2) * (A_BYTES / 2), eb * 128 + (q >> 2) * 64, (j * 4 + (q & 3)) * (PR / 4));
      }
      bulk_commit();
      TL(17);
      asm volatile("cp.async.wait_all;" ::: "memory");
      bulk_wait_read<0>();
      TL(18);
    }
  } else if (warp > 8) {
    const int t = tid - 288, w = warp - 9;
    float2* xs = (float2*)(aux + OFF_XS);
    float* red = (float*)(aux + OFF_RED);
    volatile uint32_t* misc = (volatile uint32_t*)(aux + OFF_MISC);

    const uint32_t ring = auxs + OFF_RING + w * 8192 + lane * 16;
    const uint64_t once = policy_evict_first();
    auto fetch_to = [&](uint32_t dst, const __nv_bfloat16* src, auto stepc, bool on) {
      if (on) {
#pragma unroll
        for (int k = 0; k < 4; k++) {
          if (decltype(stepc)::value == 256) cp_async16(dst + k * 512, src + k * 256);
          else cp_async16_hint(dst + k * 512, src + k * decltype(stepc)::value, once);
        }
      }
      asm volatile("cp.async.commit_group;" ::: "memory");
    };
    auto fetch = [&](int slot, const __nv_bfloat16* src, auto stepc, bool on) { fetch_to(ring + slot * 2048, src, stepc, on); };
    const int nrow = w ? 5 : 6, lrow0 = w ? 1 + 5 * w : 0;
    const int row0 = bid * 16 + lrow0;
    const __nv_bfloat16* xrow = x + (size_t)row0 * D_ + lane * 8;
    const __nv_bfloat16* wrow = wd_rows + lrow0 * D_ + lane * 8;
    const int slot4 = (OFF_XS - OFF_RING) / 2048 - 4 * w + (w ? w - 1 : 2);
    auto pace = [&](int k) {
      uint32_t it = 0;
      while ((int)lds32(kcur) < k) {
        if (++it > (1u << 20)) __trap();
        __nanosleep(50);
      }
    };
    auto fetch_row = [&](const __nv_bfloat16* p, int i) { fetch(i < 4 ? i : slot4 + i - 4, p + i * D_, IC<256>{}, i < nrow); };
    auto load_row = [&](int i, uint32_t (&xv)[16]) {
      const uint32_t a = ring + (i < 4 ? i : slot4 + i - 4) * 2048;
#pragma unroll
      for (int k = 0; k < 4; k++) {
        const uint4 v = lds128(a + k * 512);
        xv[4 * k] = v.x; xv[4 * k + 1] = v.y; xv[4 * k + 2] = v.z; xv[4 * k + 3] = v.w;
      }
    };
    mbar_wait(full0, 0);
#pragma unroll
    for (int i = 0; i < 3; i++) fetch_row(xrow, i);
    const uint32_t tag = (ld_relaxed(&g_ctr) & ~(uint32_t)(NCTA - 1)) + NCTA;
    const uint32_t tag16 = (tag >> 7) & 0xffffu, tag5 = (tag16 & 31u) << 11;
    uint32_t xo[6][16];
    auto store_row = [&](int i) {
#pragma unroll
      for (int k = 0; k < 4; k++)
        *(uint4*)(out + (size_t)(row0 + i) * D_ + lane * 8 + k * 256) = make_uint4(xo[i][4 * k], xo[i][4 * k + 1], xo[i][4 * k + 2], xo[i][4 * k + 3]);
    };
    {
      uint4 wv4[4];
#pragma unroll
      for (int k = 0; k < 4; k++) wv4[k] = __ldg((const uint4*)(w_r + lane * 8 + k * 256));
      float sh[8];
      const int ri = nrow - 1 - (lane & 7);
      float wr[32];
      float wrsum = 0.f;
#pragma unroll
      for (int k = 0; k < 4; k++) {
        const uint32_t wv[4] = {wv4[k].x, wv4[k].y, wv4[k].z, wv4[k].w};
#pragma unroll
        for (int c = 0; c < 4; c++) {
          wr[8 * k + 2 * c] = bf_lo(wv[c]);
          wr[8 * k + 2 * c + 1] = bf_hi(wv[c]);
          wrsum += wr[8 * k + 2 * c] + wr[8 * k + 2 * c + 1];
        }
      }
      wrsum = warp_sum(wrsum);
#pragma unroll
      for (int q = 0; q < 8; q++) sh[q] = 0.f;
#pragma unroll 1
      for (int i = 0; i < nrow; i++) {
        uint32_t xv[16];
        if (i + 3 < nrow) pace(LN_K0 + i);
        fetch_row(xrow, i + 3);
        cp_wait<3>();
        load_row(i, xv);
        float s0 = 0.f, s1 = 0.f, q0 = 0.f, q1 = 0.f, r0 = 0.f, r1 = 0.f;
#pragma unroll
        for (int c = 0; c < 16; c++) {
          const float a = bf_lo(xv[c]), b = bf_hi(xv[c]);
          s0 += a;
          s1 += b;
          q0 = fmaf(a, a, q0);
          q1 = fmaf(b, b, q1);
          r0 = fmaf(a, wr[2 * c], r0);
          r1 = fmaf(b, wr[2 * c + 1], r1);
        }
        float s[4] = {s0 + s1, q0 + q1, r0 + r1, 0.f};
        xreduce<2, 16>(s, lane);
        xreduce<1, 8>(s, lane);
#pragma unroll
        for (int q = 5; q > 0; q--) sh[q] = sh[q - 1];
        sh[0] = s[0];
      }
      xreduce<4, 4>(sh, lane);
      xreduce<2, 2>(sh, lane);
      xreduce<1, 1>(sh, lane);
      const float mean = __shfl_sync(0xffffffffu, sh[0], lane & 7) * (1.f / D_);
      float var = fmaf(-mean, mean, __shfl_sync(0xffffffffu, sh[0], 8 + (lane & 7)) * (1.f / D_));
      const float dot = __shfl_sync(0xffffffffu, sh[0], 16 + (lane & 7));
      if (__any_sync(0xffffffffu, mean * mean > 16.f * var)) {
#pragma unroll 1
        for (int i = 0; i < nrow; i++) {
          uint32_t xv[16];
          load_row(i, xv);
          const float m = __shfl_sync(0xffffffffu, mean, nrow - 1 - i);
          float qq = 0.f;
#pragma unroll
          for (int c = 0; c < 16; c++) {
            const float a = bf_lo(xv[c]) - m, b = bf_hi(xv[c]) - m;
            qq = fmaf(a, a, fmaf(b, b, qq));
          }
          qq = warp_sum(qq) * (1.f / D_);
          if (ri == i) var = qq;
        }
      }
      const float mb = bf_round(mean);
      const float den = bf_round(sqrt_approx(bf_round(bf_round(var) + 1e-5f)));
      const float inv = rcp_approx(den);
      if (lane < nrow) st_rec(g_stat + row0 + ri, __float_as_uint(inv), __float_as_uint(mb) | tag16);
      const uint32_t u = pack_bf16(0.f, fmaf(-mb, wrsum, dot) * inv);
      const uint32_t key = lane < nrow ? ((u ^ (0x80000000u | (uint32_t)((int32_t)u >> 31))) & 0xffff0000u) | tag5 | (uint32_t)(S_ - 1 - row0 - ri) : 0u;
      const uint32_t k0 = __reduce_max_sync(0xffffffffu, key);
      const uint32_t k1 = __reduce_max_sync(0xffffffffu, key == k0 ? 0u : key);
      if (lane == 0) { st_rec(g_cand + bid * 3 + w, k0, k1); TL(26 + w); }
      const uint32_t mi = pack_bf16(mb, inv);
      uint32_t mv[6];
#pragma unroll
      for (int i = 0; i < 6; i++) mv[i] = __shfl_sync(0xffffffffu, mi, nrow - 1 - i);
#pragma unroll
      for (int i = 0; i < 6; i++) load_row(min(i, nrow - 1), xo[i]);
#pragma unroll
      for (int i = 0; i < 6; i++) fetch_row(wrow, i);
#pragma unroll
      for (int i = 0; i < 6; i++) {
        const uint32_t mb2 = __byte_perm(mv[i], 0, 0x1010), inv2 = __byte_perm(mv[i], 0, 0x3232);
#pragma unroll
        for (int c = 0; c < 16; c++) xo[i][c] = bf2_fma(bf2_sub(xo[i][c], mb2), inv2, xo[i][c]);
        if (i < 3) store_row(i);
      }
      if (t == 0) TL(16);
#pragma unroll
      for (int q = 0; q < 8; q++) sh[q] = 0.f;
#pragma unroll 1
      for (int i0 = 0; i0 < 6; i0 += 2) {
        uint32_t xv[2][16];
        cp_wait<4>();
        asm volatile("cp.async.commit_group;\ncp.async.commit_group;" ::: "memory");
        load_row(i0, xv[0]);
        load_row(min(i0 + 1, nrow - 1), xv[1]);
        float s0 = 0.f, s1 = 0.f, s2 = 0.f, s3 = 0.f;
#pragma unroll
        for (int c = 0; c < 16; c++) { s0 += bf_lo(xv[0][c]); s1 += bf_hi(xv[0][c]); s2 += bf_lo(xv[1][c]); s3 += bf_hi(xv[1][c]); }
#pragma unroll
        for (int q = 5; q > 1; q--) sh[q] = sh[q - 2];
        sh[1] = s0 + s1;
        sh[0] = s2 + s3;
      }
      xreduce<4, 4>(sh, lane);
      xreduce<2, 2>(sh, lane);
      xreduce<1, 1>(sh, lane);
      sh[0] += __shfl_xor_sync(0xffffffffu, sh[0], 8);
      sh[0] += __shfl_xor_sync(0xffffffffu, sh[0], 16);
      if (lane < 6 && 5 - lane < nrow) st_rec(g_wsum + row0 + 5 - lane, __float_as_uint(sh[0]), tag);
    }
    const int nblk = bid < NFFN ? (w < 2 ? 11 : 10) : 0, blk0 = w == 0 ? 0 : w == 1 ? 11 : 22;
    if (t == 0) TL(2);
    const size_t guoff = (size_t)(rank * 512 + 16 * blk0 + (lane >> 3)) * F_ + (bid >> 1) * 64 + (lane & 7) * 8;
    const __nv_bfloat16 *pg = w_gate + guoff, *pu = w_up + guoff;
    auto fill = [&]() {
      pace(GU_KF);
      fetch(0, pg, IC<4 * F_>{}, nblk);
      fetch(1, pu, IC<4 * F_>{}, nblk);
      fetch(2, pg + 16 * F_, IC<4 * F_>{}, nblk);
      fetch(3, pu + 16 * F_, IC<4 * F_>{}, nblk);
      store_row(3);
      store_row(4);
      if (w == 0) store_row(5);
    };
    if (w == 0) {
      uint4 cs[4], ws[2];
      uint32_t it = 0, bad;
      auto load_ws = [&]() {
#pragma unroll
        for (int i = 0; i < 2; i++) ws[i] = ld_rec2(g_wsum + part * 1024 + eb * 128 + 2 * lane + 64 * i);
      };
      do {
#pragma unroll
        for (int i = 0; i < 4; i++) cs[i] = ld_rec2(g_stat + j * 256 + 2 * lane + 64 * i);
        bad = 0;
#pragma unroll
        for (int i = 0; i < 4; i++) bad |= ((cs[i].y ^ tag16) | (cs[i].w ^ tag16)) & 0xffffu;
      } while (poll_again(bad, it));
      load_ws();
      const uint32_t sg = (uint32_t)part << 31;
#pragma unroll
      for (int i = 0; i < 4; i++) {
        const uint32_t lo = ((cs[i].x + 0x8000u) ^ sg) >> 16;
        ((uint32_t*)(aux + OFF_COLSTAT))[32 * i + (lane & 16) + (lane & 3) * 4 + ((lane >> 2) & 3)] =
            (((uint32_t)max((int)(cs[i].z - lo + 0x8000u), 0) & 0xffff0000u) | lo) ^ sg;
        const uint32_t m0 = __byte_perm(cs[i].y, 0, 0x3232), m1 = __byte_perm(cs[i].w, 0, 0x3232);
        ((uint4*)(aux + OFF_MEAN))[64 * i + 2 * lane] = make_uint4(m0, m0, m0, m0);
        ((uint4*)(aux + OFF_MEAN))[64 * i + 2 * lane + 1] = make_uint4(m1, m1, m1, m1);
      }
      if (lane == 0) misc[0] = tag;
      while (poll_again((ws[0].y ^ tag) | (ws[0].w ^ tag) | (ws[1].y ^ tag) | (ws[1].w ^ tag), it)) load_ws();
#pragma unroll
      for (int i = 0; i < 2; i++) {
        uint32_t f[4];
#pragma unroll
        for (int h = 0; h < 2; h++) {
          const float wv = -__uint_as_float(h ? ws[i].z : ws[i].x), hi = bf_round(wv), mid = bf_round(wv - hi);
          f[2 * h] = pack_bf16(hi, mid);
          f[2 * h + 1] = pack_bf16(wv - hi - mid, 0.f);
        }
        ((uint4*)(aux + OFF_WSUM))[lane + 32 * i] = make_uint4(f[0], f[1], f[2], f[3]);
      }
      fence_proxy_async_smem();
      __syncwarp();
      if (lane == 0) { mbar_arrive(bar_stat); TL(3); }
      fill();
    } else {
      uint4 kv[6];
      uint32_t it = 0, bad;
      do {
        bad = 0;
#pragma unroll
        for (int i = 0; i < 6; i++) kv[i] = ld_rec2(g_cand + 2 * lane + 64 * i);
#pragma unroll
        for (int i = 0; i < 6; i++) bad |= (kv[i].x ^ tag5) | (kv[i].z ^ tag5);
      } while (poll_again(bad & 0xf800u, it));
      uint32_t k0 = 0, k1 = 0;
#pragma unroll
      for (int i = 0; i < 6; i++) {
        const uint32_t c0 = max(kv[i].x, kv[i].z), c1 = max(min(kv[i].x, kv[i].z), max(kv[i].y, kv[i].w));
        k1 = max(max(k1, c1), min(k0, c0));
        k0 = max(k0, c0);
      }
      const uint32_t m0 = __reduce_max_sync(0xffffffffu, k0);
      const uint32_t m1 = __reduce_max_sync(0xffffffffu, k0 == m0 ? k1 : k0);
      if (t == 32) { misc[2] = m0; misc[3] = m1; }
      {
        const int r0 = S_ - 1 - (m0 & (S_ - 1)), r1 = S_ - 1 - (m1 & (S_ - 1));
        const uint32_t* pa = (const uint32_t*)(x + (size_t)r0 * D_ + rank * 512 + (w - 1) * 256) + lane;
        const uint32_t* pb = (const uint32_t*)(x + (size_t)r1 * D_ + rank * 512 + (w - 1) * 256) + lane;
        uint32_t xa[4], xb[4];
#pragma unroll
        for (int k = 0; k < 4; k++) { xa[k] = ld_relaxed(pa + 32 * k); xb[k] = ld_relaxed(pb + 32 * k); }
        uint2 sa = ld_rec(g_stat + r0), sb = ld_rec(g_stat + r1);
        fill();
        while (poll_again(((sa.y ^ tag16) | (sb.y ^ tag16)) & 0xffffu, it)) {
          sa = ld_rec(g_stat + r0);
          sb = ld_rec(g_stat + r1);
        }
        const uint32_t ma = __byte_perm(sa.y, 0, 0x3232), mb = __byte_perm(sb.y, 0, 0x3232);
        const float ia = __uint_as_float(sa.x), ib = __uint_as_float(sb.x);
#pragma unroll
        for (int k = 0; k < 4; k++) {
          const uint32_t da = bf2_sub(xa[k], ma), db = bf2_sub(xb[k], mb);
          const uint32_t na = pack_bf16(bf_lo(da) * ia, bf_hi(da) * ia), nb = pack_bf16(bf_lo(db) * ib, bf_hi(db) * ib);
          ((float4*)xs)[(w - 1) * 128 + 32 * k + lane] = make_float4(bf_lo(na), bf_lo(nb), bf_hi(na), bf_hi(nb));
        }
      }
    }
    named_bar(1, 96);
    if (t == 0) TL(4);
    auto publish = [&]() {
      if (lane == 0) {
        if (w == 1) {
          mbar_wait(bar_ab + 8, 0);
          mbar_wait(bar_ab + 24, 0);
          fence_proxy_async_smem();
          tma_store(&maps.ab_ld, base + A_BYTES, j * 256 + 64, part * 1024 + eb * 128);
          bulk_commit();
          mbar_arrive_cluster(bar_pub + 8, rank ^ 1);
          bulk_wait<0>();
          mbar_arrive(bar_pub);
        } else {
          mbar_wait(bar_pub + (w ? 8 : 24), 0);
        }
        fence_gpu();
        st_relaxed(g_abflag + (eb * 2 + part) * 96 + w * 32 + j, tag);
        if (w == 1) asm volatile("red.relaxed.gpu.global.add.u32 [%0], 1;" ::"l"(&g_ctr) : "memory");
        TL(w == 0 ? 9 : w == 1 ? 19 : 22);
      }
      __syncwarp();
    };
    if (!nblk) publish();
    const int cb = bid & 15, kg = bid >> 4;
    const int ndn = w ? 9 : 10;
    const __nv_bfloat16* pd = w_down + (size_t)(kg * 448 + 16 * w + (lane >> 3)) * D_ + cb * 64 + (lane & 7) * 8;
    uint32_t sa = ring;
    if (nblk) {
      float ag[16], au[16];
#pragma unroll
      for (int i = 0; i < 16; i++) { ag[i] = 0.f; au[i] = 0.f; }
      const float2* xp = xs + 16 * blk0 + (lane >> 3);
      int kq = 0;
#pragma unroll 1
      for (int b = 0; b < nblk; b++) {
        float2 xv[4];
#pragma unroll
        for (int i = 0; i < 4; i++) xv[i] = xp[4 * i];
        xp += 16;
        pg += 16 * F_;
        pu += 16 * F_;
#pragma unroll
        for (int h = 0; h < 2; h++) {
          uint4 v[4];
          cp_wait<3>();
          if (kq == 0) {
            publish();
            kq = 2 * GU_K0;
          }
#pragma unroll
          for (int i = 0; i < 4; i++) v[i] = lds128(sa + i * 512);
          pace(kq++ >> 1);
          if (b + 2 < nblk) fetch_to(sa, (h ? pu : pg) + 16 * F_, IC<4 * F_>{}, true);
          else { fetch_to(sa, pd, IC<4 * D_>{}, true); pd += 48 * D_; }
          sa = ring + ((sa - ring + 2048) & 8191);
#pragma unroll
          for (int i = 0; i < 4; i++) gemv8(h ? au : ag, v[i], xv[i]);
        }
      }
      float s[32];
#pragma unroll
      for (int i = 0; i < 16; i++) { s[i] = ag[i]; s[16 + i] = au[i]; }
      xreduce<16, 16>(s, lane);
      xreduce<8, 8>(s, lane);
      mbar_wait(bar_pub + 8, 0);
      const uint32_t dst = mapa(auxs + OFF_GU + (rank * 3 + w) * 512 + (lane >> 4) * 256 + (lane & 3) * 64 + (lane & 8) * 4, (lane >> 2) & 1);
      const uint32_t dbar = mapa(bar_gu, (lane >> 2) & 1);
      st_async4(dst, s[0], s[1], s[2], s[3], dbar);
      st_async4(dst + 16, s[4], s[5], s[6], s[7], dbar);
      if (w == 0) {
        if (lane == 0) mbar_expect_tx(bar_gu, 6 * 512);
        mbar_wait(bar_gu, 0);
        const float2* r2 = (const float2*)(aux + OFF_GU) + lane;
        float2 g2 = r2[0], u2 = r2[32];
#pragma unroll
        for (int q = 1; q < 6; q++) {
          const float2 a = r2[64 * q], c = r2[64 * q + 32];
          g2.x += a.x; g2.y += a.y; u2.x += c.x; u2.y += c.y;
        }
        float hv[2];
#pragma unroll
        for (int tok = 0; tok < 2; tok++) {
          const float g = bf_round(tok ? g2.y : g2.x), u = bf_round(tok ? u2.y : u2.x);
          hv[tok] = bf_round(__fdividef(g, 1.f + __expf(-g))) * u;
        }
        st_rec(g_h + bid * 32 + lane, pack_bf16(hv[0], hv[1]), tag);
        if (lane == 0) TL(5);
      }
    } else {
#pragma unroll
      for (int u = 0; u < 4; u++) fetch(u, pd + u * 48 * D_, IC<4 * D_>{}, true);
      pd += 4 * 48 * D_;
      pace(H_K);
    }
    if (t == 64) prefetch_l2(out + (size_t)bid * 16 * D_, 16 * D_ * 2);
    if (t == 32 && kg == (cb & 7)) wait_out_init(tag);
    named_bar(1, 96);
    {
      uint4 hv[3];
      uint32_t it = 0;
      bool bad[3] = {true, true, w == 0};
      while (true) {
#pragma unroll
        for (int i = 0; i < 3; i++) if (bad[i]) hv[i] = ld_rec2(g_h + kg * 448 + 2 * (t + 96 * i));
#pragma unroll
        for (int i = 0; i < 3; i++) bad[i] = bad[i] && (hv[i].y != tag || hv[i].w != tag);
        if (!poll_again(bad[0] || bad[1] || bad[2], it)) break;
        __nanosleep(100);
      }
#pragma unroll
      for (int i = 0; i < 3; i++) {
        if (t + 96 * i < 224) ((float4*)xs)[t + 96 * i] = make_float4(bf_lo(hv[i].x), bf_hi(hv[i].x), bf_lo(hv[i].z), bf_hi(hv[i].z));
      }
    }
    named_bar(1, 96);
    if (t == 0) TL(10);
    {
      float ay[16];
#pragma unroll
      for (int q = 0; q < 16; q++) ay[q] = 0.f;
      const float2* hp = xs + 16 * w + (lane >> 3);
#pragma unroll 1
      for (int u = 0; u < ndn; u++) {
        float2 hv[4];
        uint4 v[4];
        cp_wait<3>();
#pragma unroll
        for (int i = 0; i < 4; i++) v[i] = lds128(sa + i * 512);
        fetch_to(sa, pd, IC<4 * D_>{}, u + 4 < ndn);
#pragma unroll
        for (int i = 0; i < 4; i++) hv[i] = hp[4 * i];
        hp += 48;
        sa = ring + ((sa - ring + 2048) & 8191);
        pd += 48 * D_;
#pragma unroll
        for (int i = 0; i < 4; i++) gemv8(ay, v[i], hv[i]);
      }
      xreduce<8, 16>(ay, lane);
      xreduce<4, 8>(ay, lane);
      ((float4*)red)[w * 32 + (lane & 7) * 4 + (lane >> 3)] = make_float4(ay[0], ay[1], ay[2], ay[3]);
    }
    named_bar(1, 96);
    if (t < 64) {
      const float2* r2 = (const float2*)red + t;
      const float2 a = r2[0], b = r2[64], c = r2[128];
      uint2* yp = g_yp + cb * 1024 + 2 * t;
      st_rec(yp + kg * 128, __float_as_uint(a.x + b.x + c.x), tag);
      st_rec(yp + kg * 128 + 1, __float_as_uint(a.y + b.y + c.y), tag);
      if (t == 0) TL(6);
      if (kg == (cb & 7)) {
        uint4 y[8];
        uint32_t it = 0, bad;
        do {
          bad = 0;
#pragma unroll
          for (int g = 0; g < 8; g++) { y[g] = ld_rec2(yp + g * 128); bad |= (y[g].y ^ tag) | (y[g].w ^ tag); }
        } while (poll_again(bad, it));
        float o[2];
#pragma unroll
        for (int tok = 0; tok < 2; tok++) {
          float sum = 0.f;
#pragma unroll
          for (int g = 0; g < 8; g++) sum += __uint_as_float(tok ? y[g].z : y[g].x);
          const uint32_t key = misc[2 + tok];
          const uint32_t rb = (key ^ (0x80000000u | ~(uint32_t)((int32_t)key >> 31))) & 0xffff0000u;
          o[tok] = bf_round(sum) * bf_round(__fdividef(1.f, 1.f + __expf(-__uint_as_float(rb))));
        }
        const int tok = t & 1;
        const float other = __shfl_xor_sync(0xffffffffu, tok ? o[0] : o[1], 1);
        const uint32_t v = tok ? pack_bf16(other, o[1]) : pack_bf16(o[0], other);
        asm volatile("red.relaxed.gpu.global.add.noftz.bf16x2 [%0], %1;"
                     ::"l"(out + (size_t)(S_ - 1 - (misc[2 + tok] & (S_ - 1))) * D_ + cb * 64 + t - tok), "r"(v) : "memory");
      }
    }
  } else {
    float acc[128];
    const int wg = warp >> 2, wi = warp & 3;
    const bool elect = (tid & 127) == 0;
    const uint32_t a_base = base + wg * (A_BYTES / 2);

    auto release = [&](int k) {
      if (elect && k < KT - STAGES) mbar_arrive(empty0 + 8 * (k & 3));
    };
    auto mma_step = [&](int st, int scale_d) {
      const uint64_t da = make_desc(a_base + st * A_BYTES), db = make_desc(base + OFF_B + st * B_BYTES);
      wgmma_fence();
      wgmma_n256(acc, da, db, scale_d);
      wgmma_n256(acc, da + 2, db + 2, 1);
      wgmma_n256(acc, da + 4, db + 4, 1);
      wgmma_commit();
      wgmma_n256(acc, da + 6, db + 6, 1);
      wgmma_commit();
    };
    auto stamp = [&](int k) {
      if (elect) TK(wg, k);
    };

#pragma unroll 1
    for (int k = 0; k < K1; k++) {
      if (k < CP0) {
        cp_wait<CP0 - 1>();
        asm volatile("cp.async.commit_group;" ::: "memory");
        fence_proxy_async_smem();
        named_bar(4, 256);
        if (tid == 0) mbar_arrive(full0 + 8 * k);
        stamp(k);
      } else {
        stamp(k);
        mbar_wait(full0 + 8 * (k & 3), (k >> 2) & 1);
      }
      mma_step(k & 3, k);
      wgmma_wait<2>();
      if (k) release(k - 1);
    }
    {
      mbar_wait(bar_stat, 0);
      uint32_t af[2];
#pragma unroll
      for (int h = 0; h < 2; h++) {
        af[h] = lds32(auxs + OFF_WSUM + (wg * 64 + wi * 16 + h * 8 + (lane >> 2)) * 8 + (lane & 1) * 4);
        if (lane & 2) af[h] = 0;
      }
      wgmma_fence();
      wgmma_n256_rs(acc, af[0], af[1], 0u, 0u, (uint64_t)(((auxs + OFF_MEAN) & 0x3FFFF) >> 4) | ((uint64_t)8 << 32));
      wgmma_commit();
      const uint32_t dst = __shfl_sync(0xffffffffu, a_base + (wi * 16 + (lane & 15)) * 128 + (((lane >> 4) ^ (lane & 7)) << 4), lane);
      const uint32_t cst = auxs + OFF_COLSTAT + (lane & 3) * 16;
      uint4 cn[8];
#pragma unroll
      for (int p = 0; p < 4; p++) cn[p] = lds128(cst + p * 64);
      mbar_wait(full0, 0);
      wgmma_wait<1>();
      release(K1 - 1);
      wgmma_wait<0>();
      if (elect) TL(12 + wg);
#pragma unroll
      for (int p = 0; p < 16; p++) {
        const uint32_t c0 = p & 1 ? cn[p >> 1].z : cn[p >> 1].x, c1 = p & 1 ? cn[p >> 1].w : cn[p >> 1].y;
        const float4 c = make_float4(bf_lo(c0), __uint_as_float(c0), bf_lo(c1), __uint_as_float(c1));
        stmatrix_x4((dst ^ ((p & 3) << 5)) + (p >> 2) * A_BYTES, pack_bf16(acc[8 * p] * c.x, acc[8 * p + 1] * c.y),
                    pack_bf16(acc[8 * p + 2] * c.x, acc[8 * p + 3] * c.y), pack_bf16(acc[8 * p + 4] * c.z, acc[8 * p + 5] * c.w),
                    pack_bf16(acc[8 * p + 6] * c.z, acc[8 * p + 7] * c.w));
        if (p == 3 || p == 15) {
          if (p == 3) fence_proxy_async_smem();
          __syncwarp();
          if (lane == 0) mbar_arrive(bar_ab + 16 * wg + (p & 8));
        }
        if (p == 3) {
#pragma unroll
          for (int q = 4; q < 8; q++) cn[q] = lds128(cst + q * 64);
        }
      }
      named_bar(2 + wg, 128);
    }
#pragma unroll
    for (int i = 0; i < 128; i++) asm volatile("" : "=f"(acc[i]));
    stamp(K1);
    mma_step(0, 0);
    mbar_wait(bar_ab + 16 * wg + 8, 0);
    fence_proxy_async_smem();
#pragma unroll 1
    for (int k = K1 + 1; k < KT; k++) {
      const bool hold = wg == 1 && k == KT - LEAD2;
      const bool early = hold || k == K1 + 4;
      if (early) {
        wgmma_wait<0>();
        release(k - 1);
      }
      if (hold) named_bar(4, 256);
      stamp(k);
      mbar_wait(full0 + 8 * (k & 3), (k >> 2) & 1);
      mma_step(k & 3, 1);
      if (k <= KT - STAGES) wgmma_wait<2>();
      if (!early) release(k - 1);
    }
    wgmma_wait<2>();
    named_bar(2 + wg, 128);
    wgmma_wait<0>();
    if (elect) TL(20 + wg);
    const uint32_t o0 = a_base + ((lane >> 4) * 8 + (lane & 7)) * 128 + (((2 * wi + ((lane >> 3) & 1)) ^ (lane & 7)) << 4);
#pragma unroll
    for (int p = 0; p < 16; p++) {
      if (p == 12) named_bar(2 + wg, 128);
      if (wg == 0 && p == 4) named_arrive(4, 256);
      stmatrix_x4_t(o0 + (p >> 2) * A_BYTES + (p & 3) * 2048, pack_bf16(acc[8 * p], acc[8 * p + 1]), pack_bf16(acc[8 * p + 2], acc[8 * p + 3]),
                    pack_bf16(acc[8 * p + 4], acc[8 * p + 5]), pack_bf16(acc[8 * p + 6], acc[8 * p + 7]));
      if ((p & 3) == 3 && ((OMASK >> (p >> 2)) & 1)) {
        fence_proxy_async_smem();
        __syncwarp();
        if (lane == 0) mbar_arrive(bar_out + 32 * wg + (p >> 2) * 8);
      }
    }
  }
}

typedef CUresult (*EncodeFn)(CUtensorMap*, CUtensorMapDataType, cuuint32_t, void*, const cuuint64_t*, const cuuint64_t*, const cuuint32_t*,
                             const cuuint32_t*, CUtensorMapInterleave, CUtensorMapSwizzle, CUtensorMapL2promotion, CUtensorMapFloatOOBfill);

void make_map(EncodeFn enc, CUtensorMap* m, void* ptr, uint64_t rows, uint64_t cols, uint32_t box_rows, CUtensorMapL2promotion promo,
              uint32_t box_cols = 64, CUtensorMapSwizzle sw = CU_TENSOR_MAP_SWIZZLE_128B) {
  cuuint64_t dims[2] = {cols, rows};
  cuuint64_t strides[1] = {cols * 2};
  cuuint32_t box[2] = {box_cols, box_rows};
  cuuint32_t es[2] = {1, 1};
  enc(m, CU_TENSOR_MAP_DATA_TYPE_BFLOAT16, 2, ptr, dims, strides, box, es, CU_TENSOR_MAP_INTERLEAVE_NONE, sw, promo,
      CU_TENSOR_MAP_FLOAT_OOB_FILL_NONE);
}

void make_map5(EncodeFn enc, CUtensorMap* m, void* ptr, uint64_t cols, uint32_t box_rows, uint32_t box_cols, CUtensorMapSwizzle sw) {
  cuuint64_t dims[5] = {cols, 2, 2, PG, 512 / PG};
  cuuint64_t strides[4] = {cols * 2 * 1024, cols * 2 * 512, cols * 2 * (512 / PG), cols * 2};
  cuuint32_t box[5] = {box_cols, 2, 2, PG, box_rows / (4 * PG)};
  cuuint32_t es[5] = {1, 1, 1, 1, 1};
  enc(m, CU_TENSOR_MAP_DATA_TYPE_BFLOAT16, 5, ptr, dims, strides, box, es, CU_TENSOR_MAP_INTERLEAVE_NONE, sw,
      CU_TENSOR_MAP_L2_PROMOTION_L2_128B, CU_TENSOR_MAP_FLOAT_OOB_FILL_NONE);
}

}

extern "C" void kernel_launch(void* const* d_in, const int* in_sizes, int n_in, void* d_out, int out_size) {
  (void)in_sizes; (void)n_in; (void)out_size;
  void* fn = nullptr;
  cudaDriverEntryPointQueryResult qr;
  cudaGetDriverEntryPoint("cuTensorMapEncodeTiled", &fn, cudaEnableDefault, &qr);
  EncodeFn enc = (EncodeFn)fn;
  void* ab = nullptr;
  cudaGetSymbolAddress(&ab, g_ab);
  Maps maps;
  const CUtensorMapL2promotion P256 = CU_TENSOR_MAP_L2_PROMOTION_L2_256B, P128 = CU_TENSOR_MAP_L2_PROMOTION_L2_128B;
  make_map(enc, &maps.x, d_in[0], S_, D_, 256, P256);
  for (int p = 0; p < 2; p++) {
    make_map5(enc, &maps.ws[p], d_in[1 + p], S_, 256, 64, CU_TENSOR_MAP_SWIZZLE_128B);
    make_map5(enc, &maps.ws_pf[p], d_in[1 + p], S_, 32, 128, CU_TENSOR_MAP_SWIZZLE_NONE);
  }
  make_map(enc, &maps.wd[0], d_in[3], D_, D_, 128, P256);
  make_map(enc, &maps.wd[1], d_in[4], D_, D_, 128, P256);
  make_map(enc, &maps.ab_ld, ab, 2 * D_, S_, 128, P128);
  make_map(enc, &maps.ab_st, ab, 2 * D_, S_, 64, P128);
  make_map5(enc, &maps.out, d_out, D_, 64, 64, CU_TENSOR_MAP_SWIZZLE_128B);
  cudaFuncSetAttribute(fused_kernel, cudaFuncAttributeMaxDynamicSharedMemorySize, SMEM_BYTES);
  fused_kernel<<<NCTA, 384, SMEM_BYTES, cudaStreamPerThread>>>(
      (const __nv_bfloat16*)d_in[0], (const __nv_bfloat16*)d_in[3], (const __nv_bfloat16*)d_in[4], (const __nv_bfloat16*)d_in[6],
      (const __nv_bfloat16*)d_in[7], (const __nv_bfloat16*)d_in[8], maps, (const __nv_bfloat16*)d_in[9], (__nv_bfloat16*)d_out);
}
```

```cpp
#include <cuda_runtime.h>
#include <cuda_bf16.h>
#include <cuda.h>
#include <stdint.h>

#define DEVI __device__ __forceinline__

namespace {

constexpr int S_ = 2048, D_ = 1024, F_ = 3584;
constexpr int STAGES = 4;
constexpr int A_BYTES = 128 * 64 * 2, B_BYTES = 256 * 64 * 2;
constexpr int K1 = 16, K2 = 32, KT = K1 + K2;
constexpr int NCTA = 128;
constexpr int NFFN = 112;
constexpr int CP0 = 2;
constexpr int LEAD2 = 4;
constexpr int OMASK = 11;
#define PG 4
constexpr int PR = 64 / PG;
constexpr int NMIR = 4;
constexpr int LN_K0 = 4;
constexpr int GU_KF = 15;
#define GUK 24
#define GU_K1 22
#define S1W 1
#define FW 1
#define CUT 1
#define CUTOP 1
#define GUR1 16
#define NB0 8
#define GUR 8
constexpr int GU_K0 = GUK;
constexpr int H_K = 30;
#define WSM 0x55540b6e80ull
constexpr unsigned long long WS_MASK = WSM;

constexpr int OFF_B = STAGES * A_BYTES;
constexpr int OFF_AUX = OFF_B + STAGES * B_BYTES;
constexpr int OFF_RING = 0;
constexpr int OFF_XS = OFF_RING + 3 * 8192;
constexpr int OFF_GU = OFF_XS + 4096;
constexpr int OFF_MEAN = OFF_GU;
constexpr int OFF_COLSTAT = OFF_XS + 8192;
constexpr int OFF_RED = OFF_COLSTAT;
constexpr int OFF_WSUM = OFF_COLSTAT + 512;
constexpr int OFF_FLAGS = OFF_COLSTAT + 1536;
constexpr int OFF_BAR = OFF_COLSTAT + 2048;
constexpr int OFF_MISC = OFF_BAR + 224;
constexpr int AUX_BYTES = OFF_MISC + 32;
constexpr int SMEM_BYTES = OFF_AUX + AUX_BYTES;
static_assert(SMEM_BYTES <= 232448, "smem");

template <int V> struct IC { static constexpr int value = V; };

struct Maps {
  CUtensorMap x, wd[2], ws[2], ws_h[2], ws_pf[2], ab_ld, ab_st, out;
};

__device__ __nv_bfloat16 g_ab[2 * D_ * S_];
__device__ uint2 g_stat[S_];
__device__ uint2 g_wsum[2 * D_];
__device__ uint2 g_cand[NCTA * 3];
__device__ uint2 g_h[F_];
__device__ uint2 g_yp[NCTA * 128];
__device__ __align__(128) uint32_t g_abflag[16 * 3 * 32];
__device__ uint32_t g_ctr;
#define TL(i) do {} while (0)
#define TK(r, k) do {} while (0)

#define TKP(r, k) TK(r, k)
#define TKC(k)
DEVI uint32_t smem_u32(const void* p) { return (uint32_t)__cvta_generic_to_shared(p); }
DEVI void mbar_init(uint32_t bar, uint32_t cnt) { asm volatile("mbarrier.init.shared::cta.b64 [%0], %1;" ::"r"(bar), "r"(cnt) : "memory"); }
DEVI void mbar_expect_tx(uint32_t bar, uint32_t bytes) { asm volatile("mbarrier.arrive.expect_tx.shared::cta.b64 _, [%0], %1;" ::"r"(bar), "r"(bytes) : "memory"); }
DEVI void mbar_arrive(uint32_t bar) { asm volatile("mbarrier.arrive.shared::cta.b64 _, [%0];" ::"r"(bar) : "memory"); }
DEVI void mbar_arrive_cluster(uint32_t bar, uint32_t cta) {
  asm volatile("{\n.reg .b32 ra;\nmapa.shared::cluster.u32 ra, %0, %1;\nmbarrier.arrive.shared::cluster.b64 _, [ra];\n}" ::"r"(bar), "r"(cta) : "memory");
}
DEVI uint32_t mapa(uint32_t a, uint32_t cta) { uint32_t r; asm("mapa.shared::cluster.u32 %0, %1, %2;" : "=r"(r) : "r"(a), "r"(cta)); return r; }
DEVI void st_async4(uint32_t dst, float a, float b, float c, float d, uint32_t bar) {
  asm volatile("st.async.shared::cluster.mbarrier::complete_tx::bytes.v4.f32 [%0], {%1, %2, %3, %4}, [%5];"
               ::"r"(dst), "f"(a), "f"(b), "f"(c), "f"(d), "r"(bar) : "memory");
}
DEVI bool mbar_try_wait(uint32_t bar, uint32_t parity) {
  uint32_t ok;
  asm volatile("{\n.reg .pred p;\nmbarrier.try_wait.parity.shared::cta.b64 p, [%1], %2;\nselp.u32 %0, 1, 0, p;\n}" : "=r"(ok) : "r"(bar), "r"(parity) : "memory");
  return ok;
}
DEVI bool mbar_test(uint32_t bar, uint32_t parity) {
  uint32_t ok;
  asm volatile("{\n.reg .pred p;\nmbarrier.test_wait.parity.shared::cta.b64 p, [%1], %2;\nselp.u32 %0, 1, 0, p;\n}" : "=r"(ok) : "r"(bar), "r"(parity) : "memory");
  return ok;
}
DEVI void mbar_wait(uint32_t bar, uint32_t parity) {
  uint32_t n = 0;
  while (!mbar_try_wait(bar, parity)) { if (++n > (1u << 20)) __trap(); }
}
DEVI uint64_t policy_evict_first() {
  uint64_t p;
  asm volatile("createpolicy.fractional.L2::evict_first.b64 %0, 1.0;" : "=l"(p));
  return p;
}
DEVI void tma_load(uint32_t dst, const CUtensorMap* m, int c0, int c1, uint32_t bar) {
  asm volatile("cp.async.bulk.tensor.2d.shared::cluster.global.mbarrier::complete_tx::bytes [%0], [%1, {%3, %4}], [%2];"
               ::"r"(dst), "l"(m), "r"(bar), "r"(c0), "r"(c1) : "memory");
}
DEVI void tma_load5(uint32_t dst, const CUtensorMap* m, int c0, int c4, uint32_t bar) {
  asm volatile("cp.async.bulk.tensor.5d.shared::cluster.global.mbarrier::complete_tx::bytes [%0], [%1, {%3, %5, %5, %5, %4}], [%2];"
               ::"r"(dst), "l"(m), "r"(bar), "r"(c0), "r"(c4), "r"(0) : "memory");
}
DEVI void tma_store(const CUtensorMap* m, uint32_t src, int c0, int c1) {
  asm volatile("cp.async.bulk.tensor.2d.global.shared::cta.bulk_group [%0, {%2, %3}], [%1];" ::"l"(m), "r"(src), "r"(c0), "r"(c1) : "memory");
}
DEVI void tma_red_add(const CUtensorMap* m, uint32_t src, int c0, int c1) {
  asm volatile("cp.reduce.async.bulk.tensor.5d.global.shared::cta.add.bulk_group [%0, {%2, %4, %4, %4, %3}], [%1];" ::"l"(m), "r"(src), "r"(c0), "r"(c1), "r"(0) : "memory");
}
DEVI uint4 lds128(uint32_t a) { uint4 v; asm volatile("ld.shared.v4.u32 {%0,%1,%2,%3}, [%4];" : "=r"(v.x), "=r"(v.y), "=r"(v.z), "=r"(v.w) : "r"(a) : "memory"); return v; }
DEVI uint32_t lds32(uint32_t a) { uint32_t v; asm volatile("ld.volatile.shared.u32 %0, [%1];" : "=r"(v) : "r"(a) : "memory"); return v; }
DEVI void sts32(uint32_t a, uint32_t v) { asm volatile("st.volatile.shared.u32 [%0], %1;" ::"r"(a), "r"(v) : "memory"); }
DEVI void tma_prefetch(const CUtensorMap* m, int c0, int c1) {
  asm volatile("cp.async.bulk.prefetch.tensor.5d.L2.global [%0, {%1, %3, %3, %3, %2}];" ::"l"(m), "r"(c0), "r"(c1), "r"(0) : "memory");
}
DEVI void cp_async16(uint32_t dst, const void* src) { asm volatile("cp.async.cg.shared.global [%0], [%1], 16;" ::"r"(dst), "l"(src) : "memory"); }
DEVI void cp_async16_hint(uint32_t dst, const void* src, uint64_t pol) {
  asm volatile("cp.async.cg.shared.global.L2::cache_hint [%0], [%1], 16, %2;" ::"r"(dst), "l"(src), "l"(pol) : "memory");
}
DEVI bool elect_one() {
  uint32_t p;
  asm volatile("{\n.reg .pred P;\nelect.sync _|P, 0xffffffff;\nselp.u32 %0, 1, 0, P;\n}" : "=r"(p));
  return p;
}
DEVI float sqrt_approx(float v) { float r; asm("sqrt.approx.ftz.f32 %0, %1;" : "=f"(r) : "f"(v)); return r; }
DEVI float rcp_approx(float v) { float r; asm("rcp.approx.ftz.f32 %0, %1;" : "=f"(r) : "f"(v)); return r; }
DEVI void bulk_commit() { asm volatile("cp.async.bulk.commit_group;" ::: "memory"); }
template <int N> DEVI void bulk_wait() { asm volatile("cp.async.bulk.wait_group %0;" ::"n"(N) : "memory"); }
template <int N> DEVI void bulk_wait_read() { asm volatile("cp.async.bulk.wait_group.read %0;" ::"n"(N) : "memory"); }
DEVI void fence_proxy_async() { asm volatile("fence.proxy.async.global;" ::: "memory"); }
DEVI void fence_proxy_async_smem() { asm volatile("fence.proxy.async.shared::cta;" ::: "memory"); }
DEVI void prefetch_map(const CUtensorMap* m) { asm volatile("prefetch.tensormap [%0];" ::"l"(m) : "memory"); }
DEVI void named_bar(int id, int n) { asm volatile("bar.sync %0, %1;" ::"r"(id), "r"(n) : "memory"); }
DEVI void named_arrive(int id, int n) { asm volatile("bar.arrive %0, %1;" ::"r"(id), "r"(n) : "memory"); }
DEVI void wgmma_fence() { asm volatile("wgmma.fence.sync.aligned;" ::: "memory"); }
DEVI void wgmma_commit() { asm volatile("wgmma.commit_group.sync.aligned;" ::: "memory"); }
template <int N> DEVI void wgmma_wait() { asm volatile("wgmma.wait_group.sync.aligned %0;" ::"n"(N) : "memory"); }
DEVI uint64_t make_desc(uint32_t addr) {
  return (uint64_t)((addr & 0x3FFFF) >> 4) | ((uint64_t)1 << 16) | ((uint64_t)64 << 32) | ((uint64_t)1 << 62);
}
DEVI uint32_t ld_acquire(const uint32_t* p) { uint32_t v; asm volatile("ld.acquire.gpu.global.u32 %0, [%1];" : "=r"(v) : "l"(p) : "memory"); return v; }
DEVI void fence_gpu() { asm volatile("fence.acq_rel.gpu;" ::: "memory"); }
DEVI uint32_t ld_relaxed(const uint32_t* p) { uint32_t v; asm volatile("ld.relaxed.gpu.global.u32 %0, [%1];" : "=r"(v) : "l"(p) : "memory"); return v; }
DEVI void st_rec(uint2* p, uint32_t a, uint32_t b) {
  asm volatile("{\n.reg .b64 t;\nmov.b64 t, {%1, %2};\nst.relaxed.gpu.global.b64 [%0], t;\n}" ::"l"(p), "r"(a), "r"(b) : "memory");
}
DEVI uint4 ld_rec2(const uint2* p) {
  uint4 v;
  asm volatile("{\n.reg .b64 a, b;\nld.relaxed.gpu.global.v2.b64 {a, b}, [%4];\nmov.b64 {%0, %1}, a;\nmov.b64 {%2, %3}, b;\n}"
               : "=r"(v.x), "=r"(v.y), "=r"(v.z), "=r"(v.w) : "l"(p) : "memory");
  return v;
}
DEVI uint2 ld_rec(const uint2* p) {
  uint2 v;
  asm volatile("{\n.reg .b64 a;\nld.relaxed.gpu.global.b64 a, [%2];\nmov.b64 {%0, %1}, a;\n}" : "=r"(v.x), "=r"(v.y) : "l"(p) : "memory");
  return v;
}
DEVI bool poll_again(bool bad, uint32_t& it) {
  if (!__any_sync(0xffffffffu, bad)) return false;
  if (++it > (1u << 18)) __trap();
  __nanosleep(40);
  return true;
}
DEVI void st_relaxed(uint32_t* p, uint32_t v) { asm volatile("st.relaxed.gpu.global.u32 [%0], %1;" ::"l"(p), "r"(v) : "memory"); }
DEVI uint32_t pack_bf16(float lo, float hi) { uint32_t r; asm("cvt.rn.bf16x2.f32 %0, %1, %2;" : "=r"(r) : "f"(hi), "f"(lo)); return r; }
DEVI float bf_lo(uint32_t v) { return __uint_as_float(v << 16); }
DEVI float bf_hi(uint32_t v) { return __uint_as_float(v & 0xffff0000u); }
DEVI float bf_round(float v) { return bf_hi(pack_bf16(0.f, v)); }
DEVI uint32_t bf2_sub(uint32_t a, uint32_t b) { uint32_t r; asm("sub.rn.bf16x2 %0, %1, %2;" : "=r"(r) : "r"(a), "r"(b)); return r; }
DEVI uint32_t bf2_fma(uint32_t a, uint32_t b, uint32_t c) { uint32_t r; asm("fma.rn.bf16x2 %0, %1, %2, %3;" : "=r"(r) : "r"(a), "r"(b), "r"(c)); return r; }
DEVI void prefetch_l2(const void* p, uint32_t bytes) { asm volatile("cp.async.bulk.prefetch.L2.global [%0], %1;" ::"l"(p), "r"(bytes) : "memory"); }
DEVI void stmatrix_x4(uint32_t addr, uint32_t a, uint32_t b, uint32_t c, uint32_t d) {
  asm volatile("stmatrix.sync.aligned.m8n8.x4.shared.b16 [%0], {%1,%2,%3,%4};" ::"r"(addr), "r"(a), "r"(b), "r"(c), "r"(d) : "memory");
}
DEVI void stmatrix_x4_t(uint32_t addr, uint32_t a, uint32_t b, uint32_t c, uint32_t d) {
  asm volatile("stmatrix.sync.aligned.m8n8.x4.trans.shared.b16 [%0], {%1,%2,%3,%4};" ::"r"(addr), "r"(a), "r"(b), "r"(c), "r"(d) : "memory");
}
#define RUN_BEGIN _Pragma("unroll 1") do {
#define RUN_END(v) } while (__float_as_uint(v) == 0x7fc12345u);
DEVI void gemv8(float (&acc)[16], const uint4& v, const float2 xv) {
  const uint32_t g4[4] = {v.x, v.y, v.z, v.w};
#pragma unroll
  for (int c = 0; c < 4; c++) {
    const float lo = bf_lo(g4[c]), hi = bf_hi(g4[c]);
    acc[4 * c + 0] = fmaf(lo, xv.x, acc[4 * c + 0]);
    acc[4 * c + 1] = fmaf(lo, xv.y, acc[4 * c + 1]);
    acc[4 * c + 2] = fmaf(hi, xv.x, acc[4 * c + 2]);
    acc[4 * c + 3] = fmaf(hi, xv.y, acc[4 * c + 3]);
  }
}
template <int H, int MASK, int N> DEVI void xreduce(float (&s)[N], int lane) {
  const bool up = lane & MASK;
#pragma unroll
  for (int i = 0; i < H; i++) {
    const float keep = up ? s[i + H] : s[i], send = up ? s[i] : s[i + H];
    s[i] = keep + __shfl_xor_sync(0xffffffffu, send, MASK);
  }
}
DEVI float warp_sum(float v) {
#pragma unroll
  for (int o = 16; o; o >>= 1) v += __shfl_xor_sync(0xffffffffu, v, o);
  return v;
}

#define ACC128 \
      "{%0,%1,%2,%3,%4,%5,%6,%7,%8,%9,%10,%11,%12,%13,%14,%15,%16,%17,%18,%19,%20,%21,%22,%23,%24,%25,%26,%27,%28,%29,%30,%31," \
      "%32,%33,%34,%35,%36,%37,%38,%39,%40,%41,%42,%43,%44,%45,%46,%47,%48,%49,%50,%51,%52,%53,%54,%55,%56,%57,%58,%59,%60,%61,%62,%63," \
      "%64,%65,%66,%67,%68,%69,%70,%71,%72,%73,%74,%75,%76,%77,%78,%79,%80,%81,%82,%83,%84,%85,%86,%87,%88,%89,%90,%91,%92,%93,%94,%95," \
      "%96,%97,%98,%99,%100,%101,%102,%103,%104,%105,%106,%107,%108,%109,%110,%111,%112,%113,%114,%115,%116,%117,%118,%119,%120,%121,%122,%123,%124,%125,%126,%127},"
#define R128(d) R8(d, 0), R8(d, 8), R8(d, 16), R8(d, 24), R8(d, 32), R8(d, 40), R8(d, 48), R8(d, 56), R8(d, 64), R8(d, 72), R8(d, 80), \
                R8(d, 88), R8(d, 96), R8(d, 104), R8(d, 112), R8(d, 120)
#define R8(d, i) "+f"(d[i]), "+f"(d[i + 1]), "+f"(d[i + 2]), "+f"(d[i + 3]), "+f"(d[i + 4]), "+f"(d[i + 5]), "+f"(d[i + 6]), "+f"(d[i + 7])
DEVI void wgmma_n256(float (&d)[128], uint64_t da, uint64_t db, int scale_d) {
  asm volatile("{\n.reg .pred p;\nsetp.ne.b32 p, %130, 0;\nwgmma.mma_async.sync.aligned.m64n256k16.f32.bf16.bf16 " ACC128
               " %128, %129, p, 1, 1, 0, 0;\n}\n" : R128(d) : "l"(da), "l"(db), "r"(scale_d));
}
DEVI void wgmma_n256_rs(float (&d)[128], uint32_t a0, uint32_t a1, uint32_t a2, uint32_t a3, uint64_t db) {
  asm volatile("wgmma.mma_async.sync.aligned.m64n256k16.f32.bf16.bf16 " ACC128 " {%128, %129, %130, %131}, %132, 1, 1, 1, 0;\n"
               : R128(d) : "r"(a0), "r"(a1), "r"(a2), "r"(a3), "l"(db));
}

#define ACC64 \
      "{%0,%1,%2,%3,%4,%5,%6,%7,%8,%9,%10,%11,%12,%13,%14,%15,%16,%17,%18,%19,%20,%21,%22,%23,%24,%25,%26,%27,%28,%29,%30,%31," \
      "%32,%33,%34,%35,%36,%37,%38,%39,%40,%41,%42,%43,%44,%45,%46,%47,%48,%49,%50,%51,%52,%53,%54,%55,%56,%57,%58,%59,%60,%61,%62,%63},"
template <int O> DEVI void wgmma_n128(float (&d)[128], uint64_t da, uint64_t db) {
  asm volatile("wgmma.mma_async.sync.aligned.m64n128k16.f32.bf16.bf16 " ACC64 " %64, %65, 1, 1, 1, 0, 0;\n"
               : R8(d, O), R8(d, O + 8), R8(d, O + 16), R8(d, O + 24), R8(d, O + 32), R8(d, O + 40), R8(d, O + 48), R8(d, O + 56)
               : "l"(da), "l"(db));
}

DEVI void wait_out_init(uint32_t tag) {
  uint32_t it = 0;
  while ((int32_t)(ld_acquire(&g_ctr) - tag) < 0) { if (++it > (1u << 20)) __trap(); }
}
template <int N> DEVI void cp_wait() { asm volatile("cp.async.wait_group %0;" ::"n"(N) : "memory"); }

DEVI int other_chunk(int m, int j) { return m + (m >= j); }
DEVI int p2_col(int n, int j) {
  const int m = n < 11 ? n - 4 : n < 18 ? n - 11 : (n - 18) >> 1;
  const int slab = n < 11 ? 0 : n < 18 ? 1 : 2 + (n & 1);
  return other_chunk(m, j) * 256 + slab * 64;
}

__global__ void __cluster_dims__(2, 1, 1) __launch_bounds__(384, 1)
fused_kernel(const __nv_bfloat16* __restrict__ x, const __nv_bfloat16* __restrict__ wd_re, const __nv_bfloat16* __restrict__ wd_im,
             const __nv_bfloat16* __restrict__ w_r, const __nv_bfloat16* __restrict__ w_gate, const __nv_bfloat16* __restrict__ w_up,
             const __grid_constant__ Maps maps, const __nv_bfloat16* __restrict__ w_down, __nv_bfloat16* __restrict__ out) {
  extern __shared__ __align__(1024) uint8_t smem[];
  const uint32_t base = smem_u32(smem);
  uint8_t* aux = smem + OFF_AUX;
  const uint32_t auxs = base + OFF_AUX;
  const uint32_t full0 = auxs + OFF_BAR, empty0 = full0 + 8 * STAGES, bar_stat = empty0 + 8 * STAGES, bar_ab = bar_stat + 8,
                 bar_out = bar_ab + 32, bar_pub = bar_out + 64, bar_gu = bar_pub + 16;
  const uint32_t kcur = auxs + OFF_MISC + 16;

  const int tid = threadIdx.x, lane = tid & 31;
  if (tid == 256) TL(0);
  const int warp = __shfl_sync(0xffffffffu, tid >> 5, 0);
  const int cl = blockIdx.x >> 1;
  const int pos = cl - 4 + max(((cl - 29) * 37) >> 8, 0) + ((cl - 4) >> 31 & (7 * cl + 36));
  const int bid = ((~pos & 3) * 2 + (pos >> 5)) * 16 + (pos & 4) * 2 + (((pos >> 3) + (pos >> 5)) & 3) * 2 + (blockIdx.x & 1);
  const int eb = bid & 7, part = (bid >> 3) & 1, j = bid >> 4;
  const uint32_t rank = blockIdx.x & 1;
  const __nv_bfloat16* wd_rows = (bid < 64 ? wd_re : wd_im) + (size_t)(bid & 63) * 16 * D_;

  if (tid < 256) {
    const uint32_t dst = base + (tid >> 3) * 128 + (((tid ^ (tid >> 3)) & 7) << 4);
    const __nv_bfloat16* pa = (part ? wd_im : wd_re) + (size_t)(eb * 128 + (tid >> 3)) * D_ + (tid & 7) * 8;
    const __nv_bfloat16* pb = x + (size_t)(j * 256 + (tid >> 3)) * D_ + (tid & 7) * 8;
#pragma unroll
    for (int k = 0; k < CP0; k++) {
      if (k) named_bar(4, 256);
#pragma unroll
      for (int q = 0; q < 12; q++) {
        const uint32_t d = dst + (q < 4 ? k * A_BYTES + q * 4096 : OFF_B + k * B_BYTES + (q - 4) * 4096);
        const __nv_bfloat16* p = (q < 4 ? pa + q * 32 * D_ : pb + (q - 4) * 32 * D_) + k * 64;
        cp_async16(d, p);
      }
      asm volatile("cp.async.commit_group;" ::: "memory");
      if (k == 0 && tid == 0) TL(15);
    }
  }
  if (warp == 9) ((uint4*)(aux + OFF_FLAGS))[lane] = make_uint4(0, 0, 0, 0);
  if (tid == 256) {
    prefetch_map(&maps.x);
    prefetch_map(&maps.wd[part]);
    if (base & 1023) __trap();
#pragma unroll
    for (int s = 0; s < STAGES; s++) { mbar_init(full0 + 8 * s, 1); mbar_init(empty0 + 8 * s, 2); }
    mbar_init(bar_stat, 1);
#pragma unroll
    for (int s = 0; s < 4; s++) mbar_init(bar_ab + 8 * s, 4);
    mbar_init(bar_pub, 1);
    mbar_init(bar_pub + 8, 2);
    mbar_init(bar_gu, 1);
    mbar_init(bar_pub + 24, 1);
    sts32(kcur, 0);
    mbar_init(bar_out, 1);
    mbar_init(bar_out + 8, 1);
    asm volatile("fence.mbarrier_init.release.cluster;" ::: "memory");
  }
  __syncthreads();
  asm volatile("barrier.cluster.arrive.relaxed.aligned;" ::: "memory");
  asm volatile("barrier.cluster.wait.acquire.aligned;" ::: "memory");

  if (warp == 8) {
    if (elect_one()) {
      const int arow = eb * 128;
      int pf_i = 0;
      auto prefetch_ws = [&](int k) {
        if ((WS_MASK >> k) & 1) {
          tma_prefetch(&maps.ws_pf[part], pf_i < 2 ? j * 256 + pf_i * 128 : pf_i < 9 ? other_chunk(pf_i - 2, j) * 256 : other_chunk(pf_i - 9, j) * 256 + 128,
                       (j * 8 + eb) * (PR / 8));
          pf_i++;
        }
      };
      auto load_b = [&](int st, const CUtensorMap* m, int col) { tma_load5(base + OFF_B + st * B_BYTES, m, col, j * PR, full0 + 8 * st); };
      TL(1);
#pragma unroll 1
      for (int k = CP0; k < K1 + 3; k++) {
        const int st = k & 3;
        mbar_wait(empty0 + 8 * st, ((k >> 2) & 1) ^ 1);
        TKP(2, k);
        if (k < K1) {
          mbar_expect_tx(full0 + 8 * st, A_BYTES + B_BYTES);
          tma_load(base + OFF_B + st * B_BYTES, &maps.x, k * 64, j * 256, full0 + 8 * st);
          tma_load(base + st * A_BYTES, &maps.wd[part], k * 64, arow, full0 + 8 * st);
        } else {
          mbar_expect_tx(full0 + 8 * st, B_BYTES);
          load_b(st, &maps.ws[part], j * 256 + (k - K1) * 64);
        }
        sts32(kcur, k);
        if (k == 4) { prefetch_map(&maps.ws[part]); prefetch_map(&maps.ws_pf[part]); prefetch_map(&maps.ab_ld); prefetch_map(&maps.ab_st); }
        prefetch_ws(k);
      }
      mbar_wait(bar_stat, 0);
      const uint32_t tag = lds32(auxs + OFF_MISC);
      uint32_t* flags = g_abflag + (eb * 2 + part) * 96;
      mbar_wait(empty0 + 24, 1);
      sts32(kcur, K1 + 3);
      auto put = [&](int h) {
        tma_store(&maps.ab_st, base + h * (A_BYTES / 2), j * 256 + (h >> 1) * 64, part * 1024 + arow + (h & 1) * 64);
        bulk_commit();
      };
#pragma unroll
      for (int w = 1; w >= 0; w--) {
        mbar_wait(bar_ab + 16 * w, 0);
        put(w);
      }
      TL(8);
      TKP(2, K1 + 3);
      mbar_expect_tx(full0 + 24, B_BYTES);
      load_b(3, &maps.ws[part], j * 256 + 192);
      prefetch_ws(K1 + 3);
      bulk_wait<0>();
      TL(11);
      mbar_arrive(bar_pub + 24);
      const uint32_t mirror = auxs + OFF_FLAGS;
      uint32_t mc = 0;
      auto refresh = [&](int col) {
        const int lv = min((col >> 6) & 3, 2);
        cp_async16(mirror + mc + lv * 32, flags + lv * 32);
        cp_async16(mirror + mc + lv * 32 + 16, flags + lv * 32 + 4);
        mc = (mc + 128) & (NMIR * 128 - 1);
      };
      auto ready = [&](int col) {
        const uint32_t a = mirror + min((col >> 6) & 3, 2) * 32 + (col >> 8) * 4;
        uint32_t v[NMIR];
#pragma unroll
        for (int i = 0; i < NMIR; i++) v[i] = lds32(a + i * 128);
        bool r = false;
#pragma unroll
        for (int i = 0; i < NMIR; i++) r |= v[i] == tag;
        return r;
      };
      mbar_wait(bar_ab + 8, 0);
      mbar_wait(bar_ab + 24, 0);
      fence_proxy_async_smem();
      refresh(0);
      {
        uint32_t it = 0;
        while (!mbar_test(empty0, 0)) {
          __nanosleep(150);
          refresh(0);
          if (++it > (1u << 20)) __trap();
        }
      }
#pragma unroll 1
      for (int n = 4; n < K2 - 3; n++) {
        const int k = K1 + n, st = k & 3;
        const int col = p2_col(n, j);
        mbar_wait(empty0 + 8 * st, ((k >> 2) & 1) ^ 1);
        TKP(2, k);
        mbar_expect_tx(full0 + 8 * st, A_BYTES + B_BYTES);
        load_b(st, &maps.ws[part], col);
        if (n == 4) put(4);
        uint32_t it = 3;
        while (!ready(col)) {
          if ((++it & 3) == 0) refresh(col);
          if (it > (1u << 22)) __trap();
          __nanosleep(32);
        }
        if (n == 5) mbar_wait(bar_pub, 0);
        if (n == 6) bulk_wait_read<1>();
        if (n == 7) { bulk_wait<0>(); mbar_arrive(bar_pub + 8); TL(23); }
        TKP(3, k);
        tma_load(base + st * A_BYTES, &maps.ab_ld, col, part * 1024 + arow, full0 + 8 * st);
        if (n < 7) put(n + 1);
        sts32(kcur, k);
        const int col2 = p2_col(min(n + 2, K2 - 1), j);
        if (!ready(col2)) refresh(col2);
        prefetch_ws(k);
        if (n == 20) { prefetch_map(&maps.ws_h[part]); prefetch_map(&maps.out); }
      }
      const int c1 = p2_col(K2 - 3, j), c2 = p2_col(K2 - 2, j), c3 = c2 + 64;
      auto load_h = [&](int hs, int col, int half, int st) {
        tma_load5(base + OFF_B + hs * (B_BYTES / 2), &maps.ws_h[part], col, j * PR + half * (PR / 2), full0 + 8 * st);
      };
      auto load_a = [&](uint32_t dst, int col, int st) { tma_load(dst, &maps.ab_ld, col, part * 1024 + arow, full0 + 8 * st); };
      {
        uint32_t it = 0;
        while (!ready(c2)) {
          refresh(c2);
          if (++it > (1u << 20)) __trap();
          __nanosleep(200);
        }
      }
      mbar_wait(empty0 + 8, 0);
      TKP(2, KT - 3);
      mbar_expect_tx(full0 + 8, A_BYTES + B_BYTES);
      load_h(2, c1, 0, 1);
      load_a(base + A_BYTES, c1, 1);
      load_a(base + OFF_B + 3 * (B_BYTES / 2), c3, 1);
      sts32(kcur, KT - 3);
      wait_out_init(tag);
      mbar_arrive(bar_out + 8);
      mbar_wait(empty0 + 16, 0);
      TKP(2, KT - 2);
      mbar_expect_tx(full0 + 16, A_BYTES + B_BYTES);
      load_h(4, c2, 0, 2);
      load_a(base + 2 * A_BYTES, c2, 2);
      load_h(5, c3, 0, 2);
      mbar_wait(empty0 + 24, 0);
      TKP(2, KT - 1);
      mbar_expect_tx(full0 + 24, B_BYTES);
      load_h(6, c1, 1, 3);
      load_h(7, c2, 1, 3);
      mbar_wait(empty0, 1);
      TL(17);
      mbar_expect_tx(full0, B_BYTES / 2);
      load_h(0, c3, 1, 0);
      asm volatile("cp.async.wait_all;" ::: "memory");
    }
  } else if (warp > 8) {
    const int t = tid - 288, w = warp - 9;
    float2* xs = (float2*)(aux + OFF_XS);
    float* red = (float*)(aux + OFF_RED);
    volatile uint32_t* misc = (volatile uint32_t*)(aux + OFF_MISC);

    const uint32_t ring = auxs + OFF_RING + w * 8192 + lane * 16;
    const uint64_t once = policy_evict_first();
    auto fetch_to = [&](uint32_t dst, const __nv_bfloat16* src, auto stepc, bool on) {
      if (on) {
#pragma unroll
        for (int k = 0; k < 4; k++) {
          if (decltype(stepc)::value == 256) cp_async16(dst + k * 512, src + k * 256);
          else cp_async16_hint(dst + k * 512, src + k * decltype(stepc)::value, once);
        }
      }
      asm volatile("cp.async.commit_group;" ::: "memory");
    };
    auto fetch = [&](int slot, const __nv_bfloat16* src, auto stepc, bool on) { fetch_to(ring + slot * 2048, src, stepc, on); };
    const int nrow = w ? 5 : 6, lrow0 = w ? 1 + 5 * w : 0;
    const int row0 = bid * 16 + lrow0;
    const __nv_bfloat16* xrow = x + (size_t)row0 * D_ + lane * 8;
    const __nv_bfloat16* wrow = wd_rows + lrow0 * D_ + lane * 8;
    const int slot4 = (OFF_XS - OFF_RING) / 2048 - 4 * w + (w ? w - 1 : 2);
    auto pace = [&](int k) {
      uint32_t it = 0;
      while ((int)lds32(kcur) < k) {
        if (++it > (1u << 20)) __trap();
        __nanosleep(50);
      }
    };
    auto fetch_row = [&](const __nv_bfloat16* p, int i) { fetch(i < 4 ? i : slot4 + i - 4, p + i * D_, IC<256>{}, i < nrow); };
    auto load_row = [&](int i, uint32_t (&xv)[16]) {
      const uint32_t a = ring + (i < 4 ? i : slot4 + i - 4) * 2048;
#pragma unroll
      for (int k = 0; k < 4; k++) {
        const uint4 v = lds128(a + k * 512);
        xv[4 * k] = v.x; xv[4 * k + 1] = v.y; xv[4 * k + 2] = v.z; xv[4 * k + 3] = v.w;
      }
    };
    mbar_wait(full0, 0);
#pragma unroll
    for (int i = 0; i < 3; i++) fetch_row(xrow, i);
    const uint32_t tag = (ld_relaxed(&g_ctr) & ~(uint32_t)(NCTA - 1)) + NCTA;
    const uint32_t tag16 = (tag >> 7) & 0xffffu, tag5 = (tag16 & 31u) << 11;
    uint32_t xo[6][16];
    auto store_row = [&](int i) {
#pragma unroll
      for (int k = 0; k < 4; k++)
        *(uint4*)(out + (size_t)(row0 + i) * D_ + lane * 8 + k * 256) = make_uint4(xo[i][4 * k], xo[i][4 * k + 1], xo[i][4 * k + 2], xo[i][4 * k + 3]);
    };
    {
      uint4 wv4[4];
#pragma unroll
      for (int k = 0; k < 4; k++) wv4[k] = __ldg((const uint4*)(w_r + lane * 8 + k * 256));
      float sh[8];
      const int ri = nrow - 1 - (lane & 7);
      float wr[32];
      float wrsum = 0.f;
#pragma unroll
      for (int k = 0; k < 4; k++) {
        const uint32_t wv[4] = {wv4[k].x, wv4[k].y, wv4[k].z, wv4[k].w};
#pragma unroll
        for (int c = 0; c < 4; c++) {
          wr[8 * k + 2 * c] = bf_lo(wv[c]);
          wr[8 * k + 2 * c + 1] = bf_hi(wv[c]);
          wrsum += wr[8 * k + 2 * c] + wr[8 * k + 2 * c + 1];
        }
      }
      wrsum = warp_sum(wrsum);
#pragma unroll
      for (int q = 0; q < 8; q++) sh[q] = 0.f;
#pragma unroll 1
      for (int i = 0; i < nrow; i++) {
        uint32_t xv[16];
        if (i + 3 < nrow) pace(LN_K0 + i);
        fetch_row(xrow, i + 3);
        cp_wait<3>();
        load_row(i, xv);
        float s0 = 0.f, s1 = 0.f, q0 = 0.f, q1 = 0.f, r0 = 0.f, r1 = 0.f;
#define YL 16
#pragma unroll
        for (int c0 = 0; c0 < 16; c0 += YL) {
#pragma unroll
          for (int c = c0; c < c0 + YL; c++) {
          const float a = bf_lo(xv[c]), b = bf_hi(xv[c]);
          s0 += a;
          s1 += b;
          q0 = fmaf(a, a, q0);
          q1 = fmaf(b, b, q1);
          r0 = fmaf(a, wr[2 * c], r0);
          r1 = fmaf(b, wr[2 * c + 1], r1);
          }
        }
        float s[4] = {s0 + s1, q0 + q1, r0 + r1, 0.f};
        xreduce<2, 16>(s, lane);
        xreduce<1, 8>(s, lane);
#pragma unroll
        for (int q = 5; q > 0; q--) sh[q] = sh[q - 1];
        sh[0] = s[0];
      }
      xreduce<4, 4>(sh, lane);
      xreduce<2, 2>(sh, lane);
      xreduce<1, 1>(sh, lane);
      const float mean = __shfl_sync(0xffffffffu, sh[0], lane & 7) * (1.f / D_);
      float var = fmaf(-mean, mean, __shfl_sync(0xffffffffu, sh[0], 8 + (lane & 7)) * (1.f / D_));
      const float dot = __shfl_sync(0xffffffffu, sh[0], 16 + (lane & 7));
      if (__any_sync(0xffffffffu, mean * mean > 16.f * var)) {
#pragma unroll 1
        for (int i = 0; i < nrow; i++) {
          uint32_t xv[16];
          load_row(i, xv);
          const float m = __shfl_sync(0xffffffffu, mean, nrow - 1 - i);
          float qq = 0.f;
#pragma unroll
          for (int c = 0; c < 16; c++) {
            const float a = bf_lo(xv[c]) - m, b = bf_hi(xv[c]) - m;
            qq = fmaf(a, a, fmaf(b, b, qq));
          }
          qq = warp_sum(qq) * (1.f / D_);
          if (ri == i) var = qq;
        }
      }
      const float mb = bf_round(mean);
      const float den = bf_round(sqrt_approx(bf_round(bf_round(var) + 1e-5f)));
      const float inv = rcp_approx(den);
      if (lane < nrow) st_rec(g_stat + row0 + ri, __float_as_uint(inv), __float_as_uint(mb) | tag16);
      const uint32_t u = pack_bf16(0.f, fmaf(-mb, wrsum, dot) * inv);
      const uint32_t key = lane < nrow ? ((u ^ (0x80000000u | (uint32_t)((int32_t)u >> 31))) & 0xffff0000u) | tag5 | (uint32_t)(S_ - 1 - row0 - ri) : 0u;
      const uint32_t k0 = __reduce_max_sync(0xffffffffu, key);
      const uint32_t k1 = __reduce_max_sync(0xffffffffu, key == k0 ? 0u : key);
      if (lane == 0) { st_rec(g_cand + bid * 3 + w, k0, k1); TL(26 + w); }
      const uint32_t mi = pack_bf16(mb, inv);
      uint32_t mv[6];
#pragma unroll
      for (int i = 0; i < 6; i++) mv[i] = __shfl_sync(0xffffffffu, mi, nrow - 1 - i);
#pragma unroll
      for (int i = 0; i < 6; i++) load_row(min(i, nrow - 1), xo[i]);
#pragma unroll
      for (int i = 0; i < 6; i++) fetch_row(wrow, i);
#pragma unroll
      for (int i = 0; i < 6; i++) {
        const uint32_t mb2 = __byte_perm(mv[i], 0, 0x1010), inv2 = __byte_perm(mv[i], 0, 0x3232);
#pragma unroll
        for (int c = 0; c < 16; c++) xo[i][c] = bf2_fma(bf2_sub(xo[i][c], mb2), inv2, xo[i][c]);
        if (i < 3) store_row(i);
      }
      if (t == 0) TL(16);
#pragma unroll
      for (int q = 0; q < 8; q++) sh[q] = 0.f;
#pragma unroll 1
      for (int i0 = 0; i0 < 6; i0 += 2) {
        uint32_t xv[2][16];
        cp_wait<4>();
        asm volatile("cp.async.commit_group;\ncp.async.commit_group;" ::: "memory");
        load_row(i0, xv[0]);
        load_row(min(i0 + 1, nrow - 1), xv[1]);
        float s0 = 0.f, s1 = 0.f, s2 = 0.f, s3 = 0.f;
#pragma unroll
        for (int c0 = 0; c0 < 16; c0 += YL) {
#pragma unroll
          for (int c = c0; c < c0 + YL; c++) { s0 += bf_lo(xv[0][c]); s1 += bf_hi(xv[0][c]); s2 += bf_lo(xv[1][c]); s3 += bf_hi(xv[1][c]); }
        }
#pragma unroll
        for (int q = 5; q > 1; q--) sh[q] = sh[q - 2];
        sh[1] = s0 + s1;
        sh[0] = s2 + s3;
      }
      xreduce<4, 4>(sh, lane);
      xreduce<2, 2>(sh, lane);
      xreduce<1, 1>(sh, lane);
      sh[0] += __shfl_xor_sync(0xffffffffu, sh[0], 8);
      sh[0] += __shfl_xor_sync(0xffffffffu, sh[0], 16);
      if (lane < 6 && 5 - lane < nrow) st_rec(g_wsum + row0 + 5 - lane, __float_as_uint(sh[0]), tag);
    }
    const int nblk = bid < NFFN ? (w ? (32 - NB0) / 2 : NB0) : 0, blk0 = w ? NB0 + (w - 1) * ((32 - NB0) / 2) : 0;
    if (t == 0) TL(2);
    const size_t guoff = (size_t)(rank * 512 + 16 * blk0 + (lane >> 3)) * F_ + (bid >> 1) * 64 + (lane & 7) * 8;
    const __nv_bfloat16 *pg = w_gate + guoff, *pu = w_up + guoff;
    auto fill = [&]() {
      pace(GU_KF);
      fetch(0, pg, IC<4 * F_>{}, nblk);
      fetch(1, pu, IC<4 * F_>{}, nblk);
      fetch(2, pg + 16 * F_, IC<4 * F_>{}, nblk);
      fetch(3, pu + 16 * F_, IC<4 * F_>{}, nblk);
      store_row(3);
      store_row(4);
      if (w == 0) store_row(5);
    };
    if (w == 0) {
      uint4 cs[4], ws[2];
      uint32_t it = 0, bad;
      auto load_ws = [&]() {
#pragma unroll
        for (int i = 0; i < 2; i++) ws[i] = ld_rec2(g_wsum + part * 1024 + eb * 128 + 2 * lane + 64 * i);
      };
      do {
#pragma unroll
        for (int i = 0; i < 4; i++) cs[i] = ld_rec2(g_stat + j * 256 + 2 * lane + 64 * i);
        bad = 0;
#pragma unroll
        for (int i = 0; i < 4; i++) bad |= ((cs[i].y ^ tag16) | (cs[i].w ^ tag16)) & 0xffffu;
      } while (poll_again(bad, it));
      load_ws();
      const uint32_t sg = (uint32_t)part << 31;
#pragma unroll
      for (int i = 0; i < 4; i++) {
        const uint32_t lo = ((cs[i].x + 0x8000u) ^ sg) >> 16;
        ((uint32_t*)(aux + OFF_COLSTAT))[32 * i + (lane & 16) + (lane & 3) * 4 + ((lane >> 2) & 3)] =
            (((uint32_t)max((int)(cs[i].z - lo + 0x8000u), 0) & 0xffff0000u) | lo) ^ sg;
        const uint32_t m0 = __byte_perm(cs[i].y, 0, 0x3232), m1 = __byte_perm(cs[i].w, 0, 0x3232);
        ((uint4*)(aux + OFF_MEAN))[64 * i + 2 * lane] = make_uint4(m0, m0, m0, m0);
        ((uint4*)(aux + OFF_MEAN))[64 * i + 2 * lane + 1] = make_uint4(m1, m1, m1, m1);
      }
      if (lane == 0) misc[0] = tag;
      while (poll_again((ws[0].y ^ tag) | (ws[0].w ^ tag) | (ws[1].y ^ tag) | (ws[1].w ^ tag), it)) load_ws();
#pragma unroll
      for (int i = 0; i < 2; i++) {
        uint32_t f[4];
#pragma unroll
        for (int h = 0; h < 2; h++) {
          const float wv = -__uint_as_float(h ? ws[i].z : ws[i].x), hi = bf_round(wv), mid = bf_round(wv - hi);
          f[2 * h] = pack_bf16(hi, mid);
          f[2 * h + 1] = pack_bf16(wv - hi - mid, 0.f);
        }
        ((uint4*)(aux + OFF_WSUM))[lane + 32 * i] = make_uint4(f[0], f[1], f[2], f[3]);
      }
      fence_proxy_async_smem();
      __syncwarp();
      if (lane == 0) { mbar_arrive(bar_stat); TL(3); }
      fill();
    } else {
      uint4 kv[6];
      uint32_t it = 0, bad;
      do {
        bad = 0;
#pragma unroll
        for (int i = 0; i < 6; i++) kv[i] = ld_rec2(g_cand + 2 * lane + 64 * i);
#pragma unroll
        for (int i = 0; i < 6; i++) bad |= (kv[i].x ^ tag5) | (kv[i].z ^ tag5);
      } while (poll_again(bad & 0xf800u, it));
      uint32_t k0 = 0, k1 = 0;
#pragma unroll
      for (int i = 0; i < 6; i++) {
        const uint32_t c0 = max(kv[i].x, kv[i].z), c1 = max(min(kv[i].x, kv[i].z), max(kv[i].y, kv[i].w));
        k1 = max(max(k1, c1), min(k0, c0));
        k0 = max(k0, c0);
      }
      const uint32_t m0 = __reduce_max_sync(0xffffffffu, k0);
      const uint32_t m1 = __reduce_max_sync(0xffffffffu, k0 == m0 ? k1 : k0);
      if (t == 32) { misc[2] = m0; misc[3] = m1; }
      {
        const int r0 = S_ - 1 - (m0 & (S_ - 1)), r1 = S_ - 1 - (m1 & (S_ - 1));
        const uint32_t* pa = (const uint32_t*)(x + (size_t)r0 * D_ + rank * 512 + (w - 1) * 256) + lane;
        const uint32_t* pb = (const uint32_t*)(x + (size_t)r1 * D_ + rank * 512 + (w - 1) * 256) + lane;
        uint32_t xa[4], xb[4];
#pragma unroll
        for (int k = 0; k < 4; k++) { xa[k] = ld_relaxed(pa + 32 * k); xb[k] = ld_relaxed(pb + 32 * k); }
        uint2 sa = ld_rec(g_stat + r0), sb = ld_rec(g_stat + r1);
        fill();
        while (poll_again(((sa.y ^ tag16) | (sb.y ^ tag16)) & 0xffffu, it)) {
          sa = ld_rec(g_stat + r0);
          sb = ld_rec(g_stat + r1);
        }
        const uint32_t ma = __byte_perm(sa.y, 0, 0x3232), mb = __byte_perm(sb.y, 0, 0x3232);
        const float ia = __uint_as_float(sa.x), ib = __uint_as_float(sb.x);
#pragma unroll
        for (int k = 0; k < 4; k++) {
          const uint32_t da = bf2_sub(xa[k], ma), db = bf2_sub(xb[k], mb);
          const uint32_t na = pack_bf16(bf_lo(da) * ia, bf_hi(da) * ia), nb = pack_bf16(bf_lo(db) * ib, bf_hi(db) * ib);
          ((float4*)xs)[(w - 1) * 128 + 32 * k + lane] = make_float4(bf_lo(na), bf_lo(nb), bf_hi(na), bf_hi(nb));
        }
      }
    }
    named_bar(1, 96);
    if (t == 0) TL(4);
    auto put1 = [&]() {
      mbar_wait(bar_ab + 8, 0);
      mbar_wait(bar_ab + 24, 0);
      fence_proxy_async_smem();
      tma_store(&maps.ab_ld, base + A_BYTES, j * 256 + 64, part * 1024 + eb * 128);
      bulk_commit();
      mbar_arrive_cluster(bar_pub + 8, rank ^ 1);
      bulk_wait<0>();
      mbar_arrive(bar_pub);
    };
    if (S1W && t == 32) put1();
    if (t == 0) {
      auto flag = [&](int lv) {
        fence_gpu();
        st_relaxed(g_abflag + (eb * 2 + part) * 96 + lv * 32 + j, tag);
      };
      mbar_wait(bar_pub + 24, 0);
      flag(0);
      TL(9);
      if (S1W == 0) put1();
      else mbar_wait(bar_pub, 0);
      flag(1);
      asm volatile("red.relaxed.gpu.global.add.u32 [%0], 1;" ::"l"(&g_ctr) : "memory");
      TL(19);
      mbar_wait(bar_pub + 8, 0);
      flag(2);
      TL(22);
    }
    __syncwarp();
    const int cb = bid & 15, kg = bid >> 4;
    const int ndn = w ? 9 : 10;
    const __nv_bfloat16* pd = w_down + (size_t)(kg * 448 + 16 * w + (lane >> 3)) * D_ + cb * 64 + (lane & 7) * 8;
    uint32_t sa = ring;
    if (nblk) {
      float ag[16], au[16];
#pragma unroll
      for (int i = 0; i < 16; i++) { ag[i] = 0.f; au[i] = 0.f; }
      const float2* xp = xs + 16 * blk0 + (lane >> 3);
      int kq = 16 * GU_K1;
#pragma unroll 1
      for (int b = 0; b < nblk; b++) {
        float2 xv[4];
#pragma unroll
        for (int i = 0; i < 4; i++) xv[i] = xp[4 * i];
        xp += 16;
        pg += 16 * F_;
        pu += 16 * F_;
#pragma unroll
        for (int h = 0; h < 2; h++) {
          uint4 v[4];
          cp_wait<3>();
#pragma unroll
          for (int i = 0; i < 4; i++) v[i] = lds128(sa + i * 512);
          pace(kq >> 4);
          kq += kq < 16 * GU_K0 ? GUR1 : GUR;
          if (b + 2 < nblk) fetch_to(sa, (h ? pu : pg) + 16 * F_, IC<4 * F_>{}, true);
          else { fetch_to(sa, pd, IC<4 * D_>{}, true); pd += 48 * D_; }
          sa = ring + ((sa - ring + 2048) & 8191);
#pragma unroll
          for (int i = 0; i < 4; i++) gemv8(h ? au : ag, v[i], xv[i]);
        }
      }
      float s[32];
#pragma unroll
      for (int i = 0; i < 16; i++) { s[i] = ag[i]; s[16 + i] = au[i]; }
      xreduce<16, 16>(s, lane);
      xreduce<8, 8>(s, lane);
      mbar_wait(bar_pub + 8, 0);
      const uint32_t dst = mapa(auxs + OFF_GU + (rank * 3 + w) * 512 + (lane >> 4) * 256 + (lane & 3) * 64 + (lane & 8) * 4, (lane >> 2) & 1);
      const uint32_t dbar = mapa(bar_gu, (lane >> 2) & 1);
      st_async4(dst, s[0], s[1], s[2], s[3], dbar);
      st_async4(dst + 16, s[4], s[5], s[6], s[7], dbar);
      if (w == 0) {
        if (lane == 0) mbar_expect_tx(bar_gu, 6 * 512);
        mbar_wait(bar_gu, 0);
        const float2* r2 = (const float2*)(aux + OFF_GU) + lane;
        float2 g2 = r2[0], u2 = r2[32];
#pragma unroll
        for (int q = 1; q < 6; q++) {
          const float2 a = r2[64 * q], c = r2[64 * q + 32];
          g2.x += a.x; g2.y += a.y; u2.x += c.x; u2.y += c.y;
        }
        float hv[2];
#pragma unroll
        for (int tok = 0; tok < 2; tok++) {
          const float g = bf_round(tok ? g2.y : g2.x), u = bf_round(tok ? u2.y : u2.x);
          hv[tok] = bf_round(__fdividef(g, 1.f + __expf(-g))) * u;
        }
        st_rec(g_h + bid * 32 + lane, pack_bf16(hv[0], hv[1]), tag);
        if (lane == 0) TL(5);
      }
    } else {
#pragma unroll
      for (int u = 0; u < 4; u++) fetch(u, pd + u * 48 * D_, IC<4 * D_>{}, true);
      pd += 4 * 48 * D_;
      pace(H_K);
    }
    if (t == 64) prefetch_l2(out + (size_t)bid * 16 * D_, 16 * D_ * 2);
    if (t == 32 && kg == (cb & 7)) wait_out_init(tag);
    named_bar(1, 96);
    {
      uint4 hv[3];
      uint32_t it = 0;
      bool bad[3] = {true, true, w == 0};
      while (true) {
#pragma unroll
        for (int i = 0; i < 3; i++) if (bad[i]) hv[i] = ld_rec2(g_h + kg * 448 + 2 * (t + 96 * i));
#pragma unroll
        for (int i = 0; i < 3; i++) bad[i] = bad[i] && (hv[i].y != tag || hv[i].w != tag);
        if (!poll_again(bad[0] || bad[1] || bad[2], it)) break;
        __nanosleep(100);
      }
#pragma unroll
      for (int i = 0; i < 3; i++) {
        if (t + 96 * i < 224) ((float4*)xs)[t + 96 * i] = make_float4(bf_lo(hv[i].x), bf_hi(hv[i].x), bf_lo(hv[i].z), bf_hi(hv[i].z));
      }
    }
    named_bar(1, 96);
    if (t == 0) TL(10);
    {
      float ay[16];
#pragma unroll
      for (int q = 0; q < 16; q++) ay[q] = 0.f;
      const float2* hp = xs + 16 * w + (lane >> 3);
#pragma unroll 1
      for (int u = 0; u < ndn; u++) {
        float2 hv[4];
        uint4 v[4];
        cp_wait<3>();
#pragma unroll
        for (int i = 0; i < 4; i++) v[i] = lds128(sa + i * 512);
        fetch_to(sa, pd, IC<4 * D_>{}, u + 4 < ndn);
#pragma unroll
        for (int i = 0; i < 4; i++) hv[i] = hp[4 * i];
        hp += 48;
        sa = ring + ((sa - ring + 2048) & 8191);
        pd += 48 * D_;
#pragma unroll
        for (int i = 0; i < 4; i++) gemv8(ay, v[i], hv[i]);
      }
      xreduce<8, 16>(ay, lane);
      xreduce<4, 8>(ay, lane);
      ((float4*)red)[w * 32 + (lane & 7) * 4 + (lane >> 3)] = make_float4(ay[0], ay[1], ay[2], ay[3]);
    }
    named_bar(1, 96);
    if (t < 64) {
      const float2* r2 = (const float2*)red + t;
      const float2 a = r2[0], b = r2[64], c = r2[128];
      uint2* yp = g_yp + cb * 1024 + 2 * t;
      st_rec(yp + kg * 128, __float_as_uint(a.x + b.x + c.x), tag);
      st_rec(yp + kg * 128 + 1, __float_as_uint(a.y + b.y + c.y), tag);
      if (t == 0) TL(6);
      if (kg == (cb & 7)) {
        uint4 y[8];
        uint32_t it = 0, bad;
        do {
          bad = 0;
#pragma unroll
          for (int g = 0; g < 8; g++) { y[g] = ld_rec2(yp + g * 128); bad |= (y[g].y ^ tag) | (y[g].w ^ tag); }
        } while (poll_again(bad, it));
        float o[2];
#pragma unroll
        for (int tok = 0; tok < 2; tok++) {
          float sum = 0.f;
#pragma unroll
          for (int g = 0; g < 8; g++) sum += __uint_as_float(tok ? y[g].z : y[g].x);
          const uint32_t key = misc[2 + tok];
          const uint32_t rb = (key ^ (0x80000000u | ~(uint32_t)((int32_t)key >> 31))) & 0xffff0000u;
          o[tok] = bf_round(sum) * bf_round(__fdividef(1.f, 1.f + __expf(-__uint_as_float(rb))));
        }
        const int tok = t & 1;
        const float other = __shfl_xor_sync(0xffffffffu, tok ? o[0] : o[1], 1);
        const uint32_t v = tok ? pack_bf16(other, o[1]) : pack_bf16(o[0], other);
        asm volatile("red.relaxed.gpu.global.add.noftz.bf16x2 [%0], %1;"
                     ::"l"(out + (size_t)(S_ - 1 - (misc[2 + tok] & (S_ - 1))) * D_ + cb * 64 + t - tok), "r"(v) : "memory");
        if (t == 0) TL(32);
      }
    }
  } else {
    float acc[128];
    const int wg = warp >> 2, wi = warp & 3;
    const bool elect = (tid & 127) == 0;
    const uint32_t a_base = base + wg * (A_BYTES / 2);

    auto release = [&](int k) {
      if (elect) mbar_arrive(empty0 + 8 * (k & 3));
    };
    auto mma_step = [&](int st, int scale_d) {
      const uint64_t da = make_desc(a_base + st * A_BYTES), db = make_desc(base + OFF_B + st * B_BYTES);
      wgmma_fence();
      wgmma_n256(acc, da, db, scale_d);
      wgmma_n256(acc, da + 2, db + 2, 1);
      wgmma_n256(acc, da + 4, db + 4, 1);
      wgmma_commit();
      wgmma_n256(acc, da + 6, db + 6, 1);
      wgmma_commit();
    };
    auto stamp = [&](int k) {
      if (elect) TK(wg, k);
    };

#pragma unroll 1
    for (int k = 0; k < K1; k++) {
      if (k < CP0) {
        cp_wait<CP0 - 1>();
        asm volatile("cp.async.commit_group;" ::: "memory");
        fence_proxy_async_smem();
        named_bar(4, 256);
        if (tid == 0) mbar_arrive(full0 + 8 * k);
        stamp(k);
      } else {
        stamp(k);
        mbar_wait(full0 + 8 * (k & 3), (k >> 2) & 1);
        TKC(k);
      }
      mma_step(k & 3, k);
      wgmma_wait<2>();
      if (k) release(k - 1);
    }
    {
      mbar_wait(bar_stat, 0);
      uint32_t af[2];
#pragma unroll
      for (int h = 0; h < 2; h++) {
        af[h] = lds32(auxs + OFF_WSUM + (wg * 64 + wi * 16 + h * 8 + (lane >> 2)) * 8 + (lane & 1) * 4);
        if (lane & 2) af[h] = 0;
      }
      wgmma_fence();
      wgmma_n256_rs(acc, af[0], af[1], 0u, 0u, (uint64_t)(((auxs + OFF_MEAN) & 0x3FFFF) >> 4) | ((uint64_t)8 << 32));
      wgmma_commit();
      const uint32_t dst = __shfl_sync(0xffffffffu, a_base + (wi * 16 + (lane & 15)) * 128 + (((lane >> 4) ^ (lane & 7)) << 4), lane);
      const uint32_t cst = auxs + OFF_COLSTAT + (lane & 3) * 16;
      uint4 cn[8];
#pragma unroll
      for (int p = 0; p < 4; p++) cn[p] = lds128(cst + p * 64);
      mbar_wait(full0, 0);
      wgmma_wait<1>();
      release(K1 - 1);
      wgmma_wait<0>();
      if (elect) TL(12 + wg);
#pragma unroll
      for (int p = 0; p < 16; p++) {
        const uint32_t c0 = p & 1 ? cn[p >> 1].z : cn[p >> 1].x, c1 = p & 1 ? cn[p >> 1].w : cn[p >> 1].y;
        const float4 c = make_float4(bf_lo(c0), __uint_as_float(c0), bf_lo(c1), __uint_as_float(c1));
        stmatrix_x4((dst ^ ((p & 3) << 5)) + (p >> 2) * A_BYTES, pack_bf16(acc[8 * p] * c.x, acc[8 * p + 1] * c.y),
                    pack_bf16(acc[8 * p + 2] * c.x, acc[8 * p + 3] * c.y), pack_bf16(acc[8 * p + 4] * c.z, acc[8 * p + 5] * c.w),
                    pack_bf16(acc[8 * p + 6] * c.z, acc[8 * p + 7] * c.w));
        if (p == 3 || p == 15) {
          if (p == 3) fence_proxy_async_smem();
          __syncwarp();
          if (lane == 0) mbar_arrive(bar_ab + 16 * wg + (p & 8));
        }
        if (p == 3) {
#pragma unroll
          for (int q = 4; q < 8; q++) cn[q] = lds128(cst + q * 64);
        }
      }
      named_bar(2 + wg, 128);
      if (elect) TL(29 + wg);
    }
#pragma unroll
    for (int i = 0; i < 128; i++) asm volatile("" : "=f"(acc[i]));
    stamp(K1);
    mma_step(0, 0);
    mbar_wait(bar_ab + 16 * wg + 8, 0);
    fence_proxy_async_smem();
#pragma unroll 1
    for (int k = K1 + 1; k < KT - 4; k++) {
      const bool early = k == K1 + 4;
      if (early) {
        wgmma_wait<0>();
        release(k - 1);
      }
      stamp(k);
      mbar_wait(full0 + 8 * (k & 3), (k >> 2) & 1);
      TKC(k);
      mma_step(k & 3, 1);
      wgmma_wait<2>();
      if (!early) release(k - 1);
    }
    const bool second = wg != FW;
    auto turn = [&](auto oc, int i, uint32_t a, int hs) {
      const uint64_t da = make_desc(a), db = make_desc(base + OFF_B + hs * (B_BYTES / 2));
      wgmma_fence();
#pragma unroll
      for (int q = 0; q < 4; q++) wgmma_n128<decltype(oc)::value>(acc, da + 2 * q, db + 2 * q);
      wgmma_commit();
    };
    const uint32_t a3 = base + OFF_B + 3 * (B_BYTES / 2) + wg * (A_BYTES / 2);
    const uint32_t o0 = ((lane >> 4) * 8 + (lane & 7)) * 128 + (((2 * wi + ((lane >> 3) & 1)) ^ (lane & 7)) << 4);
    auto send = [&](auto oc, uint32_t dst, uint32_t pitch) {
      constexpr int O = decltype(oc)::value;
#pragma unroll
      for (int h = 0; h < 2; h++) {
#pragma unroll
        for (int p = 0; p < 4; p++) {
          const float* v = acc + O + 32 * h + 8 * p;
          stmatrix_x4_t(dst + h * pitch + o0 + p * 2048, pack_bf16(v[0], v[1]), pack_bf16(v[2], v[3]), pack_bf16(v[4], v[5]), pack_bf16(v[6], v[7]));
        }
        fence_proxy_async_smem();
        named_bar(2 + wg, 128);
        if (elect) {
          tma_red_add(&maps.out, dst + h * pitch, eb * 128 + wg * 64, (j * 4 + O / 32 + h) * (PR / 4));
          if (h == 0) TL(24 + (O / 32) + second + 9);
        }
        __syncwarp();
      }
    };
    const uint32_t zero = __shfl_sync(0xffffffffu, lds32(kcur) >> 8, 0);
    auto cut = [&](int lo, int hi) {
      if (CUTOP == 2) {
        if (zero) {
#pragma unroll
          for (int i = lo; i < hi; i++) acc[i] *= __uint_as_float(zero);
        }
      }
      if (CUTOP == 3) {
#pragma unroll 1
        for (uint32_t r = 0; r < zero; r++) {
#pragma unroll
          for (int i = lo; i < hi; i++) acc[i] *= __uint_as_float(zero);
        }
      }
#pragma unroll
      for (int i = lo; i < hi; i++) {
        if (CUTOP == 0) acc[i] = __uint_as_float(__float_as_uint(acc[i]) ^ zero);
        if (CUTOP == 1) acc[i] *= __uint_as_float(zero | 0x3f800000u);
      }
    };
    mbar_wait(full0, 1);
    wgmma_wait<0>();
    release(KT - 5);
    if (CUT == 1 || CUT == 3) cut(0, 64);
    if (CUT == 2) cut(0, 128);
    if (CUT == 4) cut(64, 128);
    if (second) {
      mbar_wait(full0 + 8, 1);
      mbar_wait(full0 + 16, 1);
      named_bar(4, 256);
    }
    stamp(KT - 4);
    turn(IC<0>{}, 0, a_base, 0);
    if (!second) mbar_wait(full0 + 8, 1);
    turn(IC<0>{}, 1, a_base + A_BYTES, 2);
    if (!second) mbar_wait(full0 + 16, 1);
    turn(IC<0>{}, 2, a_base + 2 * A_BYTES, 4);
    wgmma_wait<2>();
    release(0);
    turn(IC<0>{}, 3, a3, 5);
    named_arrive(4 + second, 256);
    stamp(KT - 3);
    if (elect) {
      mbar_wait(bar_out + 8, 0);
      fence_proxy_async();
    }
    __syncwarp();
    mbar_wait(second ? bar_out : empty0 + 24, 0);
    wgmma_wait<2>();
    if (second) named_bar(2 + wg, 128);
    wgmma_wait<0>();
    if (elect && !second) mbar_arrive(bar_out);
    if (elect) TL(24 + second);
    send(IC<0>{}, second ? base + OFF_B + B_BYTES : base + 3 * A_BYTES, A_BYTES / 2);
    if (CUT == 1 || CUT == 5) cut(64, 128);
    mbar_wait(full0 + 24, 1);
    if (second) mbar_wait(full0, 0);
    named_bar(5 + second, 256);
    stamp(KT - 2);
    turn(IC<64>{}, 0, a_base, 1);
    turn(IC<64>{}, 1, a_base + A_BYTES, 6);
    turn(IC<64>{}, 2, a_base + 2 * A_BYTES, 7);
    if (!second) mbar_wait(full0, 0);
    turn(IC<64>{}, 3, a3, 0);
    if (!second) named_arrive(6, 256);
    stamp(KT - 1);
    wgmma_wait<2>();
    named_bar(2 + wg, 128);
    wgmma_wait<0>();
    if (elect) TL(20 + second);
    send(IC<64>{}, a_base, A_BYTES);
    if (elect) {
      bulk_commit();
      bulk_wait_read<0>();
      if (second) TL(18);
    }
  }
}

typedef CUresult (*EncodeFn)(CUtensorMap*, CUtensorMapDataType, cuuint32_t, void*, const cuuint64_t*, const cuuint64_t*, const cuuint32_t*,
                             const cuuint32_t*, CUtensorMapInterleave, CUtensorMapSwizzle, CUtensorMapL2promotion, CUtensorMapFloatOOBfill);

void make_map(EncodeFn enc, CUtensorMap* m, void* ptr, uint64_t rows, uint64_t cols, uint32_t box_rows, CUtensorMapL2promotion promo,
              uint32_t box_cols = 64, CUtensorMapSwizzle sw = CU_TENSOR_MAP_SWIZZLE_128B) {
  cuuint64_t dims[2] = {cols, rows};
  cuuint64_t strides[1] = {cols * 2};
  cuuint32_t box[2] = {box_cols, box_rows};
  cuuint32_t es[2] = {1, 1};
  enc(m, CU_TENSOR_MAP_DATA_TYPE_BFLOAT16, 2, ptr, dims, strides, box, es, CU_TENSOR_MAP_INTERLEAVE_NONE, sw, promo,
      CU_TENSOR_MAP_FLOAT_OOB_FILL_NONE);
}

void make_map5(EncodeFn enc, CUtensorMap* m, void* ptr, uint64_t cols, uint32_t box_rows, uint32_t box_cols, CUtensorMapSwizzle sw) {
  cuuint64_t dims[5] = {cols, 2, 2, PG, 512 / PG};
  cuuint64_t strides[4] = {cols * 2 * 1024, cols * 2 * 512, cols * 2 * (512 / PG), cols * 2};
  cuuint32_t box[5] = {box_cols, 2, 2, PG, box_rows / (4 * PG)};
  cuuint32_t es[5] = {1, 1, 1, 1, 1};
  enc(m, CU_TENSOR_MAP_DATA_TYPE_BFLOAT16, 5, ptr, dims, strides, box, es, CU_TENSOR_MAP_INTERLEAVE_NONE, sw,
      CU_TENSOR_MAP_L2_PROMOTION_L2_128B, CU_TENSOR_MAP_FLOAT_OOB_FILL_NONE);
}

}

extern "C" void kernel_launch(void* const* d_in, const int* in_sizes, int n_in, void* d_out, int out_size) {
  (void)in_sizes; (void)n_in; (void)out_size;
  void* fn = nullptr;
  cudaDriverEntryPointQueryResult qr;
  cudaGetDriverEntryPoint("cuTensorMapEncodeTiled", &fn, cudaEnableDefault, &qr);
  EncodeFn enc = (EncodeFn)fn;
  void* ab = nullptr;
  cudaGetSymbolAddress(&ab, g_ab);
  Maps maps;
  const CUtensorMapL2promotion P256 = CU_TENSOR_MAP_L2_PROMOTION_L2_256B, P128 = CU_TENSOR_MAP_L2_PROMOTION_L2_128B;
  make_map(enc, &maps.x, d_in[0], S_, D_, 256, P256);
  for (int p = 0; p < 2; p++) {
    make_map5(enc, &maps.ws[p], d_in[1 + p], S_, 256, 64, CU_TENSOR_MAP_SWIZZLE_128B);
    make_map5(enc, &maps.ws_h[p], d_in[1 + p], S_, 128, 64, CU_TENSOR_MAP_SWIZZLE_128B);
    make_map5(enc, &maps.ws_pf[p], d_in[1 + p], S_, 32, 128, CU_TENSOR_MAP_SWIZZLE_NONE);
  }
  make_map(enc, &maps.wd[0], d_in[3], D_, D_, 128, P256);
  make_map(enc, &maps.wd[1], d_in[4], D_, D_, 128, P256);
  make_map(enc, &maps.ab_ld, ab, 2 * D_, S_, 128, P128);
  make_map(enc, &maps.ab_st, ab, 2 * D_, S_, 64, P128);
  make_map5(enc, &maps.out, d_out, D_, 64, 64, CU_TENSOR_MAP_SWIZZLE_128B);
  cudaFuncSetAttribute(fused_kernel, cudaFuncAttributeMaxDynamicSharedMemorySize, SMEM_BYTES);
  fused_kernel<<<NCTA, 384,
      SMEM_BYTES, cudaStreamPerThread>>>(
      (const __nv_bfloat16*)d_in[0], (const __nv_bfloat16*)d_in[3], (const __nv_bfloat16*)d_in[4], (const __nv_bfloat16*)d_in[6],
      (const __nv_bfloat16*)d_in[7], (const __nv_bfloat16*)d_in[8], maps, (const __nv_bfloat16*)d_in[9], (__nv_bfloat16*)d_out);
}
```

```cpp
#include <cuda_runtime.h>
#include <cuda_bf16.h>
#include <cuda.h>
#include <stdint.h>

#define DEVI __device__ __forceinline__

namespace {

constexpr int S_ = 2048, D_ = 1024, F_ = 3584;
constexpr int STAGES = 4;
constexpr int A_BYTES = 128 * 64 * 2, B_BYTES = 256 * 64 * 2;
constexpr int K1 = 16, K2 = 32, KT = K1 + K2;
constexpr int NCTA = 128;
constexpr int NFFN = 112;
constexpr int CP0 = 2;
constexpr int LEAD2 = 4;
constexpr int OMASK = 11;
#define PG 4
constexpr int PR = 64 / PG;
constexpr int NMIR = 4;
constexpr int LN_K0 = 4;
constexpr int GU_KF = 15;
#define GUK 24
#define GU_K1 22
#define S1W 1
#define FW 1
#define CUT 1
#define CUTOP 1
#define GUR1 16
#define NB0 8
#define GUR 8
constexpr int GU_K0 = GUK;
constexpr int H_K = 30;
#define WSM 0x1a0000fff80ull
constexpr unsigned long long WS_MASK = WSM;

constexpr int OFF_B = STAGES * A_BYTES;
constexpr int OFF_AUX = OFF_B + STAGES * B_BYTES;
constexpr int OFF_RING = 0;
constexpr int OFF_XS = OFF_RING + 3 * 8192;
constexpr int OFF_GU = OFF_XS + 4096;
constexpr int OFF_MEAN = OFF_GU;
constexpr int OFF_COLSTAT = OFF_XS + 8192;
constexpr int OFF_RED = OFF_COLSTAT;
constexpr int OFF_WSUM = OFF_COLSTAT + 512;
constexpr int OFF_FLAGS = OFF_COLSTAT + 1536;
constexpr int OFF_BAR = OFF_COLSTAT + 2048;
constexpr int OFF_MISC = OFF_BAR + 224;
constexpr int AUX_BYTES = OFF_MISC + 32;
constexpr int SMEM_BYTES = OFF_AUX + AUX_BYTES;
static_assert(SMEM_BYTES <= 232448, "smem");

template <int V> struct IC { static constexpr int value = V; };

struct Maps {
  CUtensorMap x, wd[2], ws[2], ws_h[2], ws_pf[2], ab_ld, ab_st, out;
};

__device__ __nv_bfloat16 g_ab[2 * D_ * S_];
__device__ uint2 g_stat[S_];
__device__ uint2 g_wsum[2 * D_];
__device__ uint2 g_cand[NCTA * 3];
__device__ uint2 g_h[F_];
__device__ uint2 g_yp[NCTA * 128];
__device__ __align__(128) uint32_t g_abflag[16 * 3 * 32];
__device__ uint32_t g_ctr;
#define TL(i) do {} while (0)
#define TK(r, k) do {} while (0)

#define TKP(r, k) TK(r, k)
#define TKC(k)
DEVI uint32_t smem_u32(const void* p) { return (uint32_t)__cvta_generic_to_shared(p); }
DEVI void mbar_init(uint32_t bar, uint32_t cnt) { asm volatile("mbarrier.init.shared::cta.b64 [%0], %1;" ::"r"(bar), "r"(cnt) : "memory"); }
DEVI void mbar_expect_tx(uint32_t bar, uint32_t bytes) { asm volatile("mbarrier.arrive.expect_tx.shared::cta.b64 _, [%0], %1;" ::"r"(bar), "r"(bytes) : "memory"); }
DEVI void mbar_arrive(uint32_t bar) { asm volatile("mbarrier.arrive.shared::cta.b64 _, [%0];" ::"r"(bar) : "memory"); }
DEVI void mbar_arrive_cluster(uint32_t bar, uint32_t cta) {
  asm volatile("{\n.reg .b32 ra;\nmapa.shared::cluster.u32 ra, %0, %1;\nmbarrier.arrive.shared::cluster.b64 _, [ra];\n}" ::"r"(bar), "r"(cta) : "memory");
}
DEVI uint32_t mapa(uint32_t a, uint32_t cta) { uint32_t r; asm("mapa.shared::cluster.u32 %0, %1, %2;" : "=r"(r) : "r"(a), "r"(cta)); return r; }
DEVI void st_async4(uint32_t dst, float a, float b, float c, float d, uint32_t bar) {
  asm volatile("st.async.shared::cluster.mbarrier::complete_tx::bytes.v4.f32 [%0], {%1, %2, %3, %4}, [%5];"
               ::"r"(dst), "f"(a), "f"(b), "f"(c), "f"(d), "r"(bar) : "memory");
}
DEVI bool mbar_try_wait(uint32_t bar, uint32_t parity) {
  uint32_t ok;
  asm volatile("{\n.reg .pred p;\nmbarrier.try_wait.parity.shared::cta.b64 p, [%1], %2;\nselp.u32 %0, 1, 0, p;\n}" : "=r"(ok) : "r"(bar), "r"(parity) : "memory");
  return ok;
}
DEVI bool mbar_test(uint32_t bar, uint32_t parity) {
  uint32_t ok;
  asm volatile("{\n.reg .pred p;\nmbarrier.test_wait.parity.shared::cta.b64 p, [%1], %2;\nselp.u32 %0, 1, 0, p;\n}" : "=r"(ok) : "r"(bar), "r"(parity) : "memory");
  return ok;
}
DEVI void mbar_wait(uint32_t bar, uint32_t parity) {
  uint32_t n = 0;
  while (!mbar_try_wait(bar, parity)) { if (++n > (1u << 20)) __trap(); }
}
DEVI void tma_load(uint32_t dst, const CUtensorMap* m, int c0, int c1, uint32_t bar) {
  asm volatile("cp.async.bulk.tensor.2d.shared::cluster.global.mbarrier::complete_tx::bytes [%0], [%1, {%3, %4}], [%2];"
               ::"r"(dst), "l"(m), "r"(bar), "r"(c0), "r"(c1) : "memory");
}
DEVI void tma_load5(uint32_t dst, const CUtensorMap* m, int c0, int c4, uint32_t bar) {
  asm volatile("cp.async.bulk.tensor.5d.shared::cluster.global.mbarrier::complete_tx::bytes [%0], [%1, {%3, %5, %5, %5, %4}], [%2];"
               ::"r"(dst), "l"(m), "r"(bar), "r"(c0), "r"(c4), "r"(0) : "memory");
}
DEVI void tma_store(const CUtensorMap* m, uint32_t src, int c0, int c1) {
  asm volatile("cp.async.bulk.tensor.2d.global.shared::cta.bulk_group [%0, {%2, %3}], [%1];" ::"l"(m), "r"(src), "r"(c0), "r"(c1) : "memory");
}
DEVI void tma_red_add(const CUtensorMap* m, uint32_t src, int c0, int c1) {
  asm volatile("cp.reduce.async.bulk.tensor.5d.global.shared::cta.add.bulk_group [%0, {%2, %4, %4, %4, %3}], [%1];" ::"l"(m), "r"(src), "r"(c0), "r"(c1), "r"(0) : "memory");
}
DEVI uint4 lds128(uint32_t a) { uint4 v; asm volatile("ld.shared.v4.u32 {%0,%1,%2,%3}, [%4];" : "=r"(v.x), "=r"(v.y), "=r"(v.z), "=r"(v.w) : "r"(a) : "memory"); return v; }
DEVI uint32_t lds32(uint32_t a) { uint32_t v; asm volatile("ld.volatile.shared.u32 %0, [%1];" : "=r"(v) : "r"(a) : "memory"); return v; }
DEVI void sts32(uint32_t a, uint32_t v) { asm volatile("st.volatile.shared.u32 [%0], %1;" ::"r"(a), "r"(v) : "memory"); }
DEVI void tma_prefetch(const CUtensorMap* m, int c0, int c1) {
  asm volatile("cp.async.bulk.prefetch.tensor.5d.L2.global [%0, {%1, %3, %3, %3, %2}];" ::"l"(m), "r"(c0), "r"(c1), "r"(0) : "memory");
}
DEVI void cp_async16(uint32_t dst, const void* src) { asm volatile("cp.async.cg.shared.global [%0], [%1], 16;" ::"r"(dst), "l"(src) : "memory"); }
#define PFS ""
DEVI void cp_async16_once(uint32_t dst, const void* src) {
  asm volatile("{\n.reg .b64 pol;\ncreatepolicy.fractional.L2::evict_first.b64 pol, 1.0;\n"
               "cp.async.cg.shared.global.L2::cache_hint" PFS " [%0], [%1], 16, pol;\n}" ::"r"(dst), "l"(src) : "memory");
}
DEVI bool elect_one() {
  uint32_t p;
  asm volatile("{\n.reg .pred P;\nelect.sync _|P, 0xffffffff;\nselp.u32 %0, 1, 0, P;\n}" : "=r"(p));
  return p;
}
DEVI float sqrt_approx(float v) { float r; asm("sqrt.approx.ftz.f32 %0, %1;" : "=f"(r) : "f"(v)); return r; }
DEVI float rcp_approx(float v) { float r; asm("rcp.approx.ftz.f32 %0, %1;" : "=f"(r) : "f"(v)); return r; }
DEVI void bulk_commit() { asm volatile("cp.async.bulk.commit_group;" ::: "memory"); }
template <int N> DEVI void bulk_wait() { asm volatile("cp.async.bulk.wait_group %0;" ::"n"(N) : "memory"); }
template <int N> DEVI void bulk_wait_read() { asm volatile("cp.async.bulk.wait_group.read %0;" ::"n"(N) : "memory"); }
DEVI void fence_proxy_async() { asm volatile("fence.proxy.async.global;" ::: "memory"); }
DEVI void fence_proxy_async_smem() { asm volatile("fence.proxy.async.shared::cta;" ::: "memory"); }
DEVI void prefetch_map(const CUtensorMap* m) { asm volatile("prefetch.tensormap [%0];" ::"l"(m) : "memory"); }
DEVI void named_bar(int id, int n) { asm volatile("bar.sync %0, %1;" ::"r"(id), "r"(n) : "memory"); }
DEVI void named_arrive(int id, int n) { asm volatile("bar.arrive %0, %1;" ::"r"(id), "r"(n) : "memory"); }
DEVI void wgmma_fence() { asm volatile("wgmma.fence.sync.aligned;" ::: "memory"); }
DEVI void wgmma_commit() { asm volatile("wgmma.commit_group.sync.aligned;" ::: "memory"); }
template <int N> DEVI void wgmma_wait() { asm volatile("wgmma.wait_group.sync.aligned %0;" ::"n"(N) : "memory"); }
DEVI uint64_t make_desc(uint32_t addr) {
  return (uint64_t)((addr & 0x3FFFF) >> 4) | ((uint64_t)1 << 16) | ((uint64_t)64 << 32) | ((uint64_t)1 << 62);
}
DEVI uint32_t ld_acquire(const uint32_t* p) { uint32_t v; asm volatile("ld.acquire.gpu.global.u32 %0, [%1];" : "=r"(v) : "l"(p) : "memory"); return v; }
DEVI void fence_gpu() { asm volatile("fence.acq_rel.gpu;" ::: "memory"); }
DEVI uint32_t ld_relaxed(const uint32_t* p) { uint32_t v; asm volatile("ld.relaxed.gpu.global.u32 %0, [%1];" : "=r"(v) : "l"(p) : "memory"); return v; }
DEVI void st_rec(uint2* p, uint32_t a, uint32_t b) {
  asm volatile("{\n.reg .b64 t;\nmov.b64 t, {%1, %2};\nst.relaxed.gpu.global.b64 [%0], t;\n}" ::"l"(p), "r"(a), "r"(b) : "memory");
}
DEVI uint4 ld_rec2(const uint2* p) {
  uint4 v;
  asm volatile("{\n.reg .b64 a, b;\nld.relaxed.gpu.global.v2.b64 {a, b}, [%4];\nmov.b64 {%0, %1}, a;\nmov.b64 {%2, %3}, b;\n}"
               : "=r"(v.x), "=r"(v.y), "=r"(v.z), "=r"(v.w) : "l"(p) : "memory");
  return v;
}
DEVI uint2 ld_rec(const uint2* p) {
  uint2 v;
  asm volatile("{\n.reg .b64 a;\nld.relaxed.gpu.global.b64 a, [%2];\nmov.b64 {%0, %1}, a;\n}" : "=r"(v.x), "=r"(v.y) : "l"(p) : "memory");
  return v;
}
DEVI bool poll_again(bool bad, uint32_t& it) {
  if (!__any_sync(0xffffffffu, bad)) return false;
  if (++it > (1u << 18)) __trap();
  __nanosleep(40);
  return true;
}
DEVI void st_relaxed(uint32_t* p, uint32_t v) { asm volatile("st.relaxed.gpu.global.u32 [%0], %1;" ::"l"(p), "r"(v) : "memory"); }
DEVI uint32_t pack_bf16(float lo, float hi) { uint32_t r; asm("cvt.rn.bf16x2.f32 %0, %1, %2;" : "=r"(r) : "f"(hi), "f"(lo)); return r; }
DEVI float bf_lo(uint32_t v) { return __uint_as_float(v << 16); }
DEVI float bf_hi(uint32_t v) { return __uint_as_float(v & 0xffff0000u); }
DEVI float bf_round(float v) { return bf_hi(pack_bf16(0.f, v)); }
DEVI uint32_t bf2_sub(uint32_t a, uint32_t b) { uint32_t r; asm("sub.rn.bf16x2 %0, %1, %2;" : "=r"(r) : "r"(a), "r"(b)); return r; }
DEVI uint32_t bf2_fma(uint32_t a, uint32_t b, uint32_t c) { uint32_t r; asm("fma.rn.bf16x2 %0, %1, %2, %3;" : "=r"(r) : "r"(a), "r"(b), "r"(c)); return r; }
DEVI void prefetch_l2(const void* p, uint32_t bytes) { asm volatile("cp.async.bulk.prefetch.L2.global [%0], %1;" ::"l"(p), "r"(bytes) : "memory"); }
DEVI void stmatrix_x4(uint32_t addr, uint32_t a, uint32_t b, uint32_t c, uint32_t d) {
  asm volatile("stmatrix.sync.aligned.m8n8.x4.shared.b16 [%0], {%1,%2,%3,%4};" ::"r"(addr), "r"(a), "r"(b), "r"(c), "r"(d) : "memory");
}
DEVI void stmatrix_x4_t(uint32_t addr, uint32_t a, uint32_t b, uint32_t c, uint32_t d) {
  asm volatile("stmatrix.sync.aligned.m8n8.x4.trans.shared.b16 [%0], {%1,%2,%3,%4};" ::"r"(addr), "r"(a), "r"(b), "r"(c), "r"(d) : "memory");
}
#define RUN_BEGIN _Pragma("unroll 1") do {
#define RUN_END(v) } while (__float_as_uint(v) == 0x7fc12345u);
DEVI void gemv8(float (&acc)[16], const uint4& v, const float2 xv) {
  const uint32_t g4[4] = {v.x, v.y, v.z, v.w};
#pragma unroll
  for (int c = 0; c < 4; c++) {
    const float lo = bf_lo(g4[c]), hi = bf_hi(g4[c]);
    acc[4 * c + 0] = fmaf(lo, xv.x, acc[4 * c + 0]);
    acc[4 * c + 1] = fmaf(lo, xv.y, acc[4 * c + 1]);
    acc[4 * c + 2] = fmaf(hi, xv.x, acc[4 * c + 2]);
    acc[4 * c + 3] = fmaf(hi, xv.y, acc[4 * c + 3]);
  }
}
template <int H, int MASK, int N> DEVI void xreduce(float (&s)[N], int lane) {
  const bool up = lane & MASK;
#pragma unroll
  for (int i = 0; i < H; i++) {
    const float keep = up ? s[i + H] : s[i], send = up ? s[i] : s[i + H];
    s[i] = keep + __shfl_xor_sync(0xffffffffu, send, MASK);
  }
}
DEVI float warp_sum(float v) {
#pragma unroll
  for (int o = 16; o; o >>= 1) v += __shfl_xor_sync(0xffffffffu, v, o);
  return v;
}

#define ACC128 \
      "{%0,%1,%2,%3,%4,%5,%6,%7,%8,%9,%10,%11,%12,%13,%14,%15,%16,%17,%18,%19,%20,%21,%22,%23,%24,%25,%26,%27,%28,%29,%30,%31," \
      "%32,%33,%34,%35,%36,%37,%38,%39,%40,%41,%42,%43,%44,%45,%46,%47,%48,%49,%50,%51,%52,%53,%54,%55,%56,%57,%58,%59,%60,%61,%62,%63," \
      "%64,%65,%66,%67,%68,%69,%70,%71,%72,%73,%74,%75,%76,%77,%78,%79,%80,%81,%82,%83,%84,%85,%86,%87,%88,%89,%90,%91,%92,%93,%94,%95," \
      "%96,%97,%98,%99,%100,%101,%102,%103,%104,%105,%106,%107,%108,%109,%110,%111,%112,%113,%114,%115,%116,%117,%118,%119,%120,%121,%122,%123,%124,%125,%126,%127},"
#define R128(d) R8(d, 0), R8(d, 8), R8(d, 16), R8(d, 24), R8(d, 32), R8(d, 40), R8(d, 48), R8(d, 56), R8(d, 64), R8(d, 72), R8(d, 80), \
                R8(d, 88), R8(d, 96), R8(d, 104), R8(d, 112), R8(d, 120)
#define R8(d, i) "+f"(d[i]), "+f"(d[i + 1]), "+f"(d[i + 2]), "+f"(d[i + 3]), "+f"(d[i + 4]), "+f"(d[i + 5]), "+f"(d[i + 6]), "+f"(d[i + 7])
DEVI void wgmma_n256(float (&d)[128], uint64_t da, uint64_t db, int scale_d) {
  asm volatile("{\n.reg .pred p;\nsetp.ne.b32 p, %130, 0;\nwgmma.mma_async.sync.aligned.m64n256k16.f32.bf16.bf16 " ACC128
               " %128, %129, p, 1, 1, 0, 0;\n}\n" : R128(d) : "l"(da), "l"(db), "r"(scale_d));
}
DEVI void wgmma_n256_rs(float (&d)[128], uint32_t a0, uint32_t a1, uint32_t a2, uint32_t a3, uint64_t db) {
  asm volatile("wgmma.mma_async.sync.aligned.m64n256k16.f32.bf16.bf16 " ACC128 " {%128, %129, %130, %131}, %132, 1, 1, 1, 0;\n"
               : R128(d) : "r"(a0), "r"(a1), "r"(a2), "r"(a3), "l"(db));
}

#define ACC64 \
      "{%0,%1,%2,%3,%4,%5,%6,%7,%8,%9,%10,%11,%12,%13,%14,%15,%16,%17,%18,%19,%20,%21,%22,%23,%24,%25,%26,%27,%28,%29,%30,%31," \
      "%32,%33,%34,%35,%36,%37,%38,%39,%40,%41,%42,%43,%44,%45,%46,%47,%48,%49,%50,%51,%52,%53,%54,%55,%56,%57,%58,%59,%60,%61,%62,%63},"
template <int O> DEVI void wgmma_n128(float (&d)[128], uint64_t da, uint64_t db) {
  asm volatile("wgmma.mma_async.sync.aligned.m64n128k16.f32.bf16.bf16 " ACC64 " %64, %65, 1, 1, 1, 0, 0;\n"
               : R8(d, O), R8(d, O + 8), R8(d, O + 16), R8(d, O + 24), R8(d, O + 32), R8(d, O + 40), R8(d, O + 48), R8(d, O + 56)
               : "l"(da), "l"(db));
}

DEVI void wait_out_init(uint32_t tag) {
  uint32_t it = 0;
  while ((int32_t)(ld_acquire(&g_ctr) - tag) < 0) { if (++it > (1u << 20)) __trap(); }
}
template <int N> DEVI void cp_wait() { asm volatile("cp.async.wait_group %0;" ::"n"(N) : "memory"); }

DEVI int other_chunk(int m, int j) { return m + (m >= j); }
DEVI int p2_col(int n, int j) {
  const int m = n < 11 ? n - 4 : n < 18 ? n - 11 : (n - 18) >> 1;
  const int slab = n < 11 ? 0 : n < 18 ? 1 : 2 + (n & 1);
  return other_chunk(m, j) * 256 + slab * 64;
}

__global__ void __cluster_dims__(2, 1, 1) __launch_bounds__(384, 1)
fused_kernel(const __nv_bfloat16* __restrict__ x, const __nv_bfloat16* __restrict__ wd_re, const __nv_bfloat16* __restrict__ wd_im,
             const __nv_bfloat16* __restrict__ w_r, const __nv_bfloat16* __restrict__ w_gate, const __nv_bfloat16* __restrict__ w_up,
             const __grid_constant__ Maps maps, const __nv_bfloat16* __restrict__ w_down, __nv_bfloat16* __restrict__ out) {
  extern __shared__ __align__(1024) uint8_t smem[];
  const uint32_t base = smem_u32(smem);
  uint8_t* aux = smem + OFF_AUX;
  const uint32_t auxs = base + OFF_AUX;
  const uint32_t full0 = auxs + OFF_BAR, empty0 = full0 + 8 * STAGES, bar_stat = empty0 + 8 * STAGES, bar_ab = bar_stat + 8,
                 bar_out = bar_ab + 32, bar_pub = bar_out + 64, bar_gu = bar_pub + 16;
  const uint32_t kcur = auxs + OFF_MISC + 16;

  const int tid = threadIdx.x, lane = tid & 31;
  if (tid == 256) TL(0);
  const int warp = __shfl_sync(0xffffffffu, tid >> 5, 0);
  const int cl = blockIdx.x >> 1;
  const int pos = cl - 4 + max(((cl - 29) * 37) >> 8, 0) + ((cl - 4) >> 31 & (7 * cl + 36));
  const int bid = ((~pos & 3) * 2 + (pos >> 5)) * 16 + (pos & 4) * 2 + (((pos >> 3) + (pos >> 5)) & 3) * 2 + (blockIdx.x & 1);
  const int eb = bid & 7, part = (bid >> 3) & 1, j = bid >> 4;
  const uint32_t rank = blockIdx.x & 1;
  const __nv_bfloat16* wd_rows = (bid < 64 ? wd_re : wd_im) + (size_t)(bid & 63) * 16 * D_;

  if (tid < 256) {
    const uint32_t dst = base + (tid >> 3) * 128 + (((tid ^ (tid >> 3)) & 7) << 4);
    const __nv_bfloat16* pa = (part ? wd_im : wd_re) + (size_t)(eb * 128 + (tid >> 3)) * D_ + (tid & 7) * 8;
    const __nv_bfloat16* pb = x + (size_t)(j * 256 + (tid >> 3)) * D_ + (tid & 7) * 8;
#pragma unroll
    for (int k = 0; k < CP0; k++) {
      if (k) named_bar(4, 256);
#pragma unroll
      for (int q = 0; q < 12; q++) {
        const uint32_t d = dst + (q < 4 ? k * A_BYTES + q * 4096 : OFF_B + k * B_BYTES + (q - 4) * 4096);
        const __nv_bfloat16* p = (q < 4 ? pa + q * 32 * D_ : pb + (q - 4) * 32 * D_) + k * 64;
        cp_async16(d, p);
      }
      asm volatile("cp.async.commit_group;" ::: "memory");
      if (k == 0 && tid == 0) TL(15);
    }
  }
  if (warp == 9) ((uint4*)(aux + OFF_FLAGS))[lane] = make_uint4(0, 0, 0, 0);
  if (tid == 256) {
    prefetch_map(&maps.x);
    prefetch_map(&maps.wd[part]);
    if (base & 1023) __trap();
#pragma unroll
    for (int s = 0; s < STAGES; s++) { mbar_init(full0 + 8 * s, 1); mbar_init(empty0 + 8 * s, 2); }
    mbar_init(bar_stat, 1);
#pragma unroll
    for (int s = 0; s < 4; s++) mbar_init(bar_ab + 8 * s, 4);
    mbar_init(bar_pub, 1);
    mbar_init(bar_pub + 8, 2);
    mbar_init(bar_gu, 1);
    mbar_init(bar_pub + 24, 1);
    sts32(kcur, 0);
    mbar_init(bar_out, 1);
    mbar_init(bar_out + 8, 1);
    asm volatile("fence.mbarrier_init.release.cluster;" ::: "memory");
  }
  __syncthreads();
  asm volatile("barrier.cluster.arrive.relaxed.aligned;" ::: "memory");
  asm volatile("barrier.cluster.wait.acquire.aligned;" ::: "memory");

  if (warp == 8) {
    if (elect_one()) {
      const int arow = eb * 128;
      int pf_i = 0;
      auto prefetch_ws = [&](int k) {
        if ((WS_MASK >> k) & 1) {
          tma_prefetch(&maps.ws_pf[part], pf_i < 2 ? j * 256 + pf_i * 128 : pf_i < 9 ? other_chunk(pf_i - 2, j) * 256 : other_chunk(pf_i - 9, j) * 256 + 128,
                       (j * 8 + eb) * (PR / 8));
          pf_i++;
        }
      };
      auto load_b = [&](int st, const CUtensorMap* m, int col) { tma_load5(base + OFF_B + st * B_BYTES, m, col, j * PR, full0 + 8 * st); };
      TL(1);
#pragma unroll 1
      for (int k = CP0; k < K1 + 3; k++) {
        const int st = k & 3;
        mbar_wait(empty0 + 8 * st, ((k >> 2) & 1) ^ 1);
        TKP(2, k);
        if (k < K1) {
          mbar_expect_tx(full0 + 8 * st, A_BYTES + B_BYTES);
          tma_load(base + OFF_B + st * B_BYTES, &maps.x, k * 64, j * 256, full0 + 8 * st);
          tma_load(base + st * A_BYTES, &maps.wd[part], k * 64, arow, full0 + 8 * st);
        } else {
          mbar_expect_tx(full0 + 8 * st, B_BYTES);
          load_b(st, &maps.ws[part], j * 256 + (k - K1) * 64);
        }
        sts32(kcur, k);
        if (k == 4) { prefetch_map(&maps.ws[part]); prefetch_map(&maps.ws_pf[part]); prefetch_map(&maps.ab_ld); prefetch_map(&maps.ab_st); }
        prefetch_ws(k);
      }
      mbar_wait(bar_stat, 0);
      const uint32_t tag = lds32(auxs + OFF_MISC);
      uint32_t* flags = g_abflag + (eb * 2 + part) * 96;
      mbar_wait(empty0 + 24, 1);
      sts32(kcur, K1 + 3);
      auto put = [&](int h) {
        tma_store(&maps.ab_st, base + h * (A_BYTES / 2), j * 256 + (h >> 1) * 64, part * 1024 + arow + (h & 1) * 64);
        bulk_commit();
      };
#pragma unroll
      for (int w = 1; w >= 0; w--) {
        mbar_wait(bar_ab + 16 * w, 0);
        put(w);
      }
      TL(8);
      TKP(2, K1 + 3);
      mbar_expect_tx(full0 + 24, B_BYTES);
      load_b(3, &maps.ws[part], j * 256 + 192);
      prefetch_ws(K1 + 3);
      bulk_wait<0>();
      TL(11);
      mbar_arrive(bar_pub + 24);
      const uint32_t mirror = auxs + OFF_FLAGS;
      uint32_t mc = 0;
      auto refresh = [&](int col) {
        const int lv = min((col >> 6) & 3, 2);
        cp_async16(mirror + mc + lv * 32, flags + lv * 32);
        cp_async16(mirror + mc + lv * 32 + 16, flags + lv * 32 + 4);
        mc = (mc + 128) & (NMIR * 128 - 1);
      };
      auto ready = [&](int col) {
        const uint32_t a = mirror + min((col >> 6) & 3, 2) * 32 + (col >> 8) * 4;
        uint32_t v[NMIR];
#pragma unroll
        for (int i = 0; i < NMIR; i++) v[i] = lds32(a + i * 128);
        bool r = false;
#pragma unroll
        for (int i = 0; i < NMIR; i++) r |= v[i] == tag;
        return r;
      };
      mbar_wait(bar_ab + 8, 0);
      mbar_wait(bar_ab + 24, 0);
      fence_proxy_async_smem();
      refresh(0);
      {
        uint32_t it = 0;
        while (!mbar_test(empty0, 0)) {
          __nanosleep(150);
          refresh(0);
          if (++it > (1u << 20)) __trap();
        }
      }
#pragma unroll 1
      for (int n = 4; n < K2 - 3; n++) {
        const int k = K1 + n, st = k & 3;
        const int col = p2_col(n, j);
        mbar_wait(empty0 + 8 * st, ((k >> 2) & 1) ^ 1);
        TKP(2, k);
        mbar_expect_tx(full0 + 8 * st, A_BYTES + B_BYTES);
        load_b(st, &maps.ws[part], col);
        if (n == 4) put(4);
        uint32_t it = 3;
        while (!ready(col)) {
          if ((++it & 3) == 0) refresh(col);
          if (it > (1u << 22)) __trap();
          __nanosleep(32);
        }
        if (n == 5) mbar_wait(bar_pub, 0);
        if (n == 6) bulk_wait_read<1>();
        if (n == 7) { bulk_wait<0>(); mbar_arrive(bar_pub + 8); TL(23); }
        TKP(3, k);
        tma_load(base + st * A_BYTES, &maps.ab_ld, col, part * 1024 + arow, full0 + 8 * st);
        if (n < 7) put(n + 1);
        sts32(kcur, k);
        const int col2 = p2_col(min(n + 2, K2 - 1), j);
        if (!ready(col2)) refresh(col2);
        prefetch_ws(k);
        if (n == 20) { prefetch_map(&maps.ws_h[part]); prefetch_map(&maps.out); }
      }
      const int c1 = p2_col(K2 - 3, j), c2 = p2_col(K2 - 2, j), c3 = c2 + 64;
      auto load_h = [&](int hs, int col, int half, int st) {
        tma_load5(base + OFF_B + hs * (B_BYTES / 2), &maps.ws_h[part], col, j * PR + half * (PR / 2), full0 + 8 * st);
      };
      auto load_a = [&](uint32_t dst, int col, int st) { tma_load(dst, &maps.ab_ld, col, part * 1024 + arow, full0 + 8 * st); };
      {
        uint32_t it = 0;
        while (!ready(c2)) {
          refresh(c2);
          if (++it > (1u << 20)) __trap();
          __nanosleep(200);
        }
      }
      mbar_wait(empty0 + 8, 0);
      TKP(2, KT - 3);
      mbar_expect_tx(full0 + 8, A_BYTES + B_BYTES);
      load_h(2, c1, 0, 1);
      load_a(base + A_BYTES, c1, 1);
      load_a(base + OFF_B + 3 * (B_BYTES / 2), c3, 1);
      sts32(kcur, KT - 3);
      wait_out_init(tag);
      mbar_arrive(bar_out + 8);
      mbar_wait(empty0 + 16, 0);
      TKP(2, KT - 2);
      mbar_expect_tx(full0 + 16, A_BYTES + B_BYTES);
      load_h(4, c2, 0, 2);
      load_a(base + 2 * A_BYTES, c2, 2);
      load_h(5, c3, 0, 2);
      mbar_wait(empty0 + 24, 0);
      TKP(2, KT - 1);
      mbar_expect_tx(full0 + 24, B_BYTES);
      load_h(6, c1, 1, 3);
      load_h(7, c2, 1, 3);
      mbar_wait(empty0, 1);
      TL(17);
      mbar_expect_tx(full0, B_BYTES / 2);
      load_h(0, c3, 1, 0);
      asm volatile("cp.async.wait_all;" ::: "memory");
    }
  } else if (warp > 8) {
    const int t = tid - 288, w = warp - 9;
    float2* xs = (float2*)(aux + OFF_XS);
    float* red = (float*)(aux + OFF_RED);
    volatile uint32_t* misc = (volatile uint32_t*)(aux + OFF_MISC);

    const uint32_t ring = auxs + OFF_RING + w * 8192 + lane * 16;
    auto fetch_to = [&](uint32_t dst, const __nv_bfloat16* src, auto stepc, bool on) {
      if (on) {
#pragma unroll
        for (int k = 0; k < 4; k++) {
          if (decltype(stepc)::value == 256) cp_async16(dst + k * 512, src + k * 256);
          else cp_async16_once(dst + k * 512, src + k * decltype(stepc)::value);
        }
      }
      asm volatile("cp.async.commit_group;" ::: "memory");
    };
    auto fetch = [&](int slot, const __nv_bfloat16* src, auto stepc, bool on) { fetch_to(ring + slot * 2048, src, stepc, on); };
    const int nrow = w ? 5 : 6, lrow0 = w ? 1 + 5 * w : 0;
    const int row0 = bid * 16 + lrow0;
    const __nv_bfloat16* xrow = x + (size_t)row0 * D_ + lane * 8;
    const __nv_bfloat16* wrow = wd_rows + lrow0 * D_ + lane * 8;
    const int slot4 = (OFF_XS - OFF_RING) / 2048 - 4 * w + (w ? w - 1 : 2);
    auto pace = [&](int k) {
      uint32_t it = 0;
      while ((int)lds32(kcur) < k) {
        if (++it > (1u << 20)) __trap();
        __nanosleep(50);
      }
    };
    auto fetch_row = [&](const __nv_bfloat16* p, int i) { fetch(i < 4 ? i : slot4 + i - 4, p + i * D_, IC<256>{}, i < nrow); };
    auto load_row = [&](int i, uint32_t (&xv)[16]) {
      const uint32_t a = ring + (i < 4 ? i : slot4 + i - 4) * 2048;
#pragma unroll
      for (int k = 0; k < 4; k++) {
        const uint4 v = lds128(a + k * 512);
        xv[4 * k] = v.x; xv[4 * k + 1] = v.y; xv[4 * k + 2] = v.z; xv[4 * k + 3] = v.w;
      }
    };
    mbar_wait(full0, 0);
#pragma unroll
    for (int i = 0; i < 3; i++) fetch_row(xrow, i);
    const uint32_t tag = (ld_relaxed(&g_ctr) & ~(uint32_t)(NCTA - 1)) + NCTA;
    const uint32_t tag16 = (tag >> 7) & 0xffffu, tag5 = (tag16 & 31u) << 11;
    uint32_t xo[6][16];
    auto store_row = [&](int i) {
#pragma unroll
      for (int k = 0; k < 4; k++)
        *(uint4*)(out + (size_t)(row0 + i) * D_ + lane * 8 + k * 256) = make_uint4(xo[i][4 * k], xo[i][4 * k + 1], xo[i][4 * k + 2], xo[i][4 * k + 3]);
    };
    {
      uint4 wv4[4];
#pragma unroll
      for (int k = 0; k < 4; k++) wv4[k] = __ldg((const uint4*)(w_r + lane * 8 + k * 256));
      float sh[8];
      const int ri = nrow - 1 - (lane & 7);
      float wr[32];
      float wrsum = 0.f;
#pragma unroll
      for (int k = 0; k < 4; k++) {
        const uint32_t wv[4] = {wv4[k].x, wv4[k].y, wv4[k].z, wv4[k].w};
#pragma unroll
        for (int c = 0; c < 4; c++) {
          wr[8 * k + 2 * c] = bf_lo(wv[c]);
          wr[8 * k + 2 * c + 1] = bf_hi(wv[c]);
          wrsum += wr[8 * k + 2 * c] + wr[8 * k + 2 * c + 1];
        }
      }
      wrsum = warp_sum(wrsum);
#pragma unroll
      for (int q = 0; q < 8; q++) sh[q] = 0.f;
#pragma unroll 1
      for (int i = 0; i < nrow; i++) {
        uint32_t xv[16];
        if (i + 3 < nrow) pace(LN_K0 + i);
        fetch_row(xrow, i + 3);
        cp_wait<3>();
        load_row(i, xv);
        float s0 = 0.f, s1 = 0.f, q0 = 0.f, q1 = 0.f, r0 = 0.f, r1 = 0.f;
#define YL 16
#pragma unroll
        for (int c0 = 0; c0 < 16; c0 += YL) {
#pragma unroll
          for (int c = c0; c < c0 + YL; c++) {
          const float a = bf_lo(xv[c]), b = bf_hi(xv[c]);
          s0 += a;
          s1 += b;
          q0 = fmaf(a, a, q0);
          q1 = fmaf(b, b, q1);
          r0 = fmaf(a, wr[2 * c], r0);
          r1 = fmaf(b, wr[2 * c + 1], r1);
          }
        }
        float s[4] = {s0 + s1, q0 + q1, r0 + r1, 0.f};
        xreduce<2, 16>(s, lane);
        xreduce<1, 8>(s, lane);
#pragma unroll
        for (int q = 5; q > 0; q--) sh[q] = sh[q - 1];
        sh[0] = s[0];
      }
      xreduce<4, 4>(sh, lane);
      xreduce<2, 2>(sh, lane);
      xreduce<1, 1>(sh, lane);
      const float mean = __shfl_sync(0xffffffffu, sh[0], lane & 7) * (1.f / D_);
      float var = fmaf(-mean, mean, __shfl_sync(0xffffffffu, sh[0], 8 + (lane & 7)) * (1.f / D_));
      const float dot = __shfl_sync(0xffffffffu, sh[0], 16 + (lane & 7));
      if (__any_sync(0xffffffffu, mean * mean > 16.f * var)) {
#pragma unroll 1
        for (int i = 0; i < nrow; i++) {
          uint32_t xv[16];
          load_row(i, xv);
          const float m = __shfl_sync(0xffffffffu, mean, nrow - 1 - i);
          float qq = 0.f;
#pragma unroll
          for (int c = 0; c < 16; c++) {
            const float a = bf_lo(xv[c]) - m, b = bf_hi(xv[c]) - m;
            qq = fmaf(a, a, fmaf(b, b, qq));
          }
          qq = warp_sum(qq) * (1.f / D_);
          if (ri == i) var = qq;
        }
      }
      const float mb = bf_round(mean);
      const float den = bf_round(sqrt_approx(bf_round(bf_round(var) + 1e-5f)));
      const float inv = rcp_approx(den);
      if (lane < nrow) st_rec(g_stat + row0 + ri, __float_as_uint(inv), __float_as_uint(mb) | tag16);
      const uint32_t u = pack_bf16(0.f, fmaf(-mb, wrsum, dot) * inv);
      const uint32_t key = lane < nrow ? ((u ^ (0x80000000u | (uint32_t)((int32_t)u >> 31))) & 0xffff0000u) | tag5 | (uint32_t)(S_ - 1 - row0 - ri) : 0u;
      const uint32_t k0 = __reduce_max_sync(0xffffffffu, key);
      const uint32_t k1 = __reduce_max_sync(0xffffffffu, key == k0 ? 0u : key);
      if (lane == 0) { st_rec(g_cand + bid * 3 + w, k0, k1); TL(26 + w); }
      const uint32_t mi = pack_bf16(mb, inv);
      uint32_t mv[6];
#pragma unroll
      for (int i = 0; i < 6; i++) mv[i] = __shfl_sync(0xffffffffu, mi, nrow - 1 - i);
#pragma unroll
      for (int i = 0; i < 6; i++) load_row(min(i, nrow - 1), xo[i]);
#pragma unroll
      for (int i = 0; i < 6; i++) fetch_row(wrow, i);
#pragma unroll
      for (int i = 0; i < 6; i++) {
        const uint32_t mb2 = __byte_perm(mv[i], 0, 0x1010), inv2 = __byte_perm(mv[i], 0, 0x3232);
#pragma unroll
        for (int c = 0; c < 16; c++) xo[i][c] = bf2_fma(bf2_sub(xo[i][c], mb2), inv2, xo[i][c]);
        if (i < 3) store_row(i);
      }
      if (t == 0) TL(16);
#pragma unroll
      for (int q = 0; q < 8; q++) sh[q] = 0.f;
#pragma unroll 1
      for (int i0 = 0; i0 < 6; i0 += 2) {
        uint32_t xv[2][16];
        cp_wait<4>();
        asm volatile("cp.async.commit_group;\ncp.async.commit_group;" ::: "memory");
        load_row(i0, xv[0]);
        load_row(min(i0 + 1, nrow - 1), xv[1]);
        float s0 = 0.f, s1 = 0.f, s2 = 0.f, s3 = 0.f;
#pragma unroll
        for (int c0 = 0; c0 < 16; c0 += YL) {
#pragma unroll
          for (int c = c0; c < c0 + YL; c++) { s0 += bf_lo(xv[0][c]); s1 += bf_hi(xv[0][c]); s2 += bf_lo(xv[1][c]); s3 += bf_hi(xv[1][c]); }
        }
#pragma unroll
        for (int q = 5; q > 1; q--) sh[q] = sh[q - 2];
        sh[1] = s0 + s1;
        sh[0] = s2 + s3;
      }
      xreduce<4, 4>(sh, lane);
      xreduce<2, 2>(sh, lane);
      xreduce<1, 1>(sh, lane);
      sh[0] += __shfl_xor_sync(0xffffffffu, sh[0], 8);
      sh[0] += __shfl_xor_sync(0xffffffffu, sh[0], 16);
      if (lane < 6 && 5 - lane < nrow) st_rec(g_wsum + row0 + 5 - lane, __float_as_uint(sh[0]), tag);
    }
    const int nblk = bid < NFFN ? (w ? (32 - NB0) / 2 : NB0) : 0, blk0 = w ? NB0 + (w - 1) * ((32 - NB0) / 2) : 0;
    if (t == 0) TL(2);
    const size_t guoff = (size_t)(rank * 512 + 16 * blk0 + (lane >> 3)) * F_ + (bid >> 1) * 64 + (lane & 7) * 8;
    const __nv_bfloat16 *pg = w_gate + guoff, *pu = w_up + guoff;
    auto fill = [&]() {
      pace(GU_KF);
      fetch(0, pg, IC<4 * F_>{}, nblk);
      fetch(1, pu, IC<4 * F_>{}, nblk);
      fetch(2, pg + 16 * F_, IC<4 * F_>{}, nblk);
      fetch(3, pu + 16 * F_, IC<4 * F_>{}, nblk);
      store_row(3);
      store_row(4);
      if (w == 0) store_row(5);
    };
    if (w == 0) {
      uint4 cs[4], ws[2];
      uint32_t it = 0, bad;
      auto load_ws = [&]() {
#pragma unroll
        for (int i = 0; i < 2; i++) ws[i] = ld_rec2(g_wsum + part * 1024 + eb * 128 + 2 * lane + 64 * i);
      };
      do {
#pragma unroll
        for (int i = 0; i < 4; i++) cs[i] = ld_rec2(g_stat + j * 256 + 2 * lane + 64 * i);
        bad = 0;
#pragma unroll
        for (int i = 0; i < 4; i++) bad |= ((cs[i].y ^ tag16) | (cs[i].w ^ tag16)) & 0xffffu;
      } while (poll_again(bad, it));
      load_ws();
      const uint32_t sg = (uint32_t)part << 31;
#pragma unroll
      for (int i = 0; i < 4; i++) {
        const uint32_t lo = ((cs[i].x + 0x8000u) ^ sg) >> 16;
        ((uint32_t*)(aux + OFF_COLSTAT))[32 * i + (lane & 16) + (lane & 3) * 4 + ((lane >> 2) & 3)] =
            (((uint32_t)max((int)(cs[i].z - lo + 0x8000u), 0) & 0xffff0000u) | lo) ^ sg;
        const uint32_t m0 = __byte_perm(cs[i].y, 0, 0x3232), m1 = __byte_perm(cs[i].w, 0, 0x3232);
        ((uint4*)(aux + OFF_MEAN))[64 * i + 2 * lane] = make_uint4(m0, m0, m0, m0);
        ((uint4*)(aux + OFF_MEAN))[64 * i + 2 * lane + 1] = make_uint4(m1, m1, m1, m1);
      }
      if (lane == 0) misc[0] = tag;
      while (poll_again((ws[0].y ^ tag) | (ws[0].w ^ tag) | (ws[1].y ^ tag) | (ws[1].w ^ tag), it)) load_ws();
#pragma unroll
      for (int i = 0; i < 2; i++) {
        uint32_t f[4];
#pragma unroll
        for (int h = 0; h < 2; h++) {
          const float wv = -__uint_as_float(h ? ws[i].z : ws[i].x), hi = bf_round(wv), mid = bf_round(wv - hi);
          f[2 * h] = pack_bf16(hi, mid);
          f[2 * h + 1] = pack_bf16(wv - hi - mid, 0.f);
        }
        ((uint4*)(aux + OFF_WSUM))[lane + 32 * i] = make_uint4(f[0], f[1], f[2], f[3]);
      }
      fence_proxy_async_smem();
      __syncwarp();
      if (lane == 0) { mbar_arrive(bar_stat); TL(3); }
      fill();
    } else {
      uint4 kv[6];
      uint32_t it = 0, bad;
      do {
        bad = 0;
#pragma unroll
        for (int i = 0; i < 6; i++) kv[i] = ld_rec2(g_cand + 2 * lane + 64 * i);
#pragma unroll
        for (int i = 0; i < 6; i++) bad |= (kv[i].x ^ tag5) | (kv[i].z ^ tag5);
      } while (poll_again(bad & 0xf800u, it));
      uint32_t k0 = 0, k1 = 0;
#pragma unroll
      for (int i = 0; i < 6; i++) {
        const uint32_t c0 = max(kv[i].x, kv[i].z), c1 = max(min(kv[i].x, kv[i].z), max(kv[i].y, kv[i].w));
        k1 = max(max(k1, c1), min(k0, c0));
        k0 = max(k0, c0);
      }
      const uint32_t m0 = __reduce_max_sync(0xffffffffu, k0);
      const uint32_t m1 = __reduce_max_sync(0xffffffffu, k0 == m0 ? k1 : k0);
      if (t == 32) { misc[2] = m0; misc[3] = m1; }
      {
        const int r0 = S_ - 1 - (m0 & (S_ - 1)), r1 = S_ - 1 - (m1 & (S_ - 1));
        const uint32_t* pa = (const uint32_t*)(x + (size_t)r0 * D_ + rank * 512 + (w - 1) * 256) + lane;
        const uint32_t* pb = (const uint32_t*)(x + (size_t)r1 * D_ + rank * 512 + (w - 1) * 256) + lane;
        uint32_t xa[4], xb[4];
#pragma unroll
        for (int k = 0; k < 4; k++) { xa[k] = ld_relaxed(pa + 32 * k); xb[k] = ld_relaxed(pb + 32 * k); }
        uint2 sa = ld_rec(g_stat + r0), sb = ld_rec(g_stat + r1);
        fill();
        while (poll_again(((sa.y ^ tag16) | (sb.y ^ tag16)) & 0xffffu, it)) {
          sa = ld_rec(g_stat + r0);
          sb = ld_rec(g_stat + r1);
        }
        const uint32_t ma = __byte_perm(sa.y, 0, 0x3232), mb = __byte_perm(sb.y, 0, 0x3232);
        const float ia = __uint_as_float(sa.x), ib = __uint_as_float(sb.x);
#pragma unroll
        for (int k = 0; k < 4; k++) {
          const uint32_t da = bf2_sub(xa[k], ma), db = bf2_sub(xb[k], mb);
          const uint32_t na = pack_bf16(bf_lo(da) * ia, bf_hi(da) * ia), nb = pack_bf16(bf_lo(db) * ib, bf_hi(db) * ib);
          ((float4*)xs)[(w - 1) * 128 + 32 * k + lane] = make_float4(bf_lo(na), bf_lo(nb), bf_hi(na), bf_hi(nb));
        }
      }
    }
    named_bar(1, 96);
    if (t == 0) TL(4);
    auto put1 = [&]() {
      mbar_wait(bar_ab + 8, 0);
      mbar_wait(bar_ab + 24, 0);
      fence_proxy_async_smem();
      tma_store(&maps.ab_ld, base + A_BYTES, j * 256 + 64, part * 1024 + eb * 128);
      bulk_commit();
      mbar_arrive_cluster(bar_pub + 8, rank ^ 1);
      bulk_wait<0>();
      mbar_arrive(bar_pub);
    };
    if (S1W && t == 32) put1();
    if (t == 0) {
      auto flag = [&](int lv) {
        fence_gpu();
        st_relaxed(g_abflag + (eb * 2 + part) * 96 + lv * 32 + j, tag);
      };
      mbar_wait(bar_pub + 24, 0);
      flag(0);
      TL(9);
      if (S1W == 0) put1();
      else mbar_wait(bar_pub, 0);
      flag(1);
      asm volatile("red.relaxed.gpu.global.add.u32 [%0], 1;" ::"l"(&g_ctr) : "memory");
      TL(19);
      mbar_wait(bar_pub + 8, 0);
      flag(2);
      TL(22);
    }
    __syncwarp();
    const int cb = bid & 15, kg = bid >> 4;
    const int ndn = w ? 9 : 10;
    const __nv_bfloat16* pd = w_down + (size_t)(kg * 448 + 16 * w + (lane >> 3)) * D_ + cb * 64 + (lane & 7) * 8;
    uint32_t sa = ring;
    uint4 v0[4], v1[4];
    float2 xv[4] = {};
    auto take = [&](uint4 (&v)[4]) {
      cp_wait<3>();
#pragma unroll
      for (int i = 0; i < 4; i++) v[i] = lds128(sa + i * 512);
    };
    auto next_down = [&](bool on) {
      fetch_to(sa, pd, IC<4 * D_>{}, on);
      pd += 48 * D_;
    };
    auto half = [&](float (&acc)[16], const uint4 (&v)[4], int h) {
      gemv8(acc, v[2 * h], xv[2 * h]);
      gemv8(acc, v[2 * h + 1], xv[2 * h + 1]);
    };
    if (nblk) {
      float ag[16], au[16];
#pragma unroll
      for (int i = 0; i < 16; i++) { ag[i] = 0.f; au[i] = 0.f; }
      const float2* xp = xs + 16 * blk0 + (lane >> 3);
      int kq = 16 * GU_K1;
      auto refill = [&](int kc, const __nv_bfloat16* p, bool gu) {
        if (kc < (kq >> 4)) pace(kq >> 4);
        kq += kq < 16 * GU_K0 ? GUR1 : GUR;
        if (gu) fetch_to(sa, p, IC<4 * F_>{}, true);
        else next_down(true);
        sa = ring + ((sa - ring + 2048) & 8191);
      };
      take(v0);
      xv[0] = xp[0];
      xv[1] = xp[4];
      pg += 32 * F_;
      pu += 32 * F_;
      refill(0, pg, true);
#pragma unroll 1
      for (int b = 0; b < nblk; b++) {
        take(v1);
        int kc = lds32(kcur);
        xv[2] = xp[8];
        xv[3] = xp[12];
        xp += 16;
        pg += 16 * F_;
        half(ag, v0, 0);
        refill(kc, pu, b + 2 < nblk);
        half(ag, v0, 1);
        take(v0);
        kc = lds32(kcur);
        pu += 16 * F_;
        half(au, v1, 0);
        xv[0] = xp[0];
        xv[1] = xp[4];
        refill(kc, pg, b + 3 < nblk);
        half(au, v1, 1);
      }
      float s[32];
#pragma unroll
      for (int i = 0; i < 16; i++) { s[i] = ag[i]; s[16 + i] = au[i]; }
      xreduce<16, 16>(s, lane);
      xreduce<8, 8>(s, lane);
      mbar_wait(bar_pub + 8, 0);
      const uint32_t dst = mapa(auxs + OFF_GU + (rank * 3 + w) * 512 + (lane >> 4) * 256 + (lane & 3) * 64 + (lane & 8) * 4, (lane >> 2) & 1);
      const uint32_t dbar = mapa(bar_gu, (lane >> 2) & 1);
      st_async4(dst, s[0], s[1], s[2], s[3], dbar);
      st_async4(dst + 16, s[4], s[5], s[6], s[7], dbar);
      if (w == 0) {
        if (lane == 0) mbar_expect_tx(bar_gu, 6 * 512);
        mbar_wait(bar_gu, 0);
        const float2* r2 = (const float2*)(aux + OFF_GU) + lane;
        float2 g2 = r2[0], u2 = r2[32];
#pragma unroll
        for (int q = 1; q < 6; q++) {
          const float2 a = r2[64 * q], c = r2[64 * q + 32];
          g2.x += a.x; g2.y += a.y; u2.x += c.x; u2.y += c.y;
        }
        float hv[2];
#pragma unroll
        for (int tok = 0; tok < 2; tok++) {
          const float g = bf_round(tok ? g2.y : g2.x), u = bf_round(tok ? u2.y : u2.x);
          hv[tok] = bf_round(__fdividef(g, 1.f + __expf(-g))) * u;
        }
        st_rec(g_h + bid * 32 + lane, pack_bf16(hv[0], hv[1]), tag);
        if (lane == 0) TL(5);
      }
    } else {
#pragma unroll
      for (int u = 0; u < 4; u++) fetch(u, pd + u * 48 * D_, IC<4 * D_>{}, true);
      pd += 4 * 48 * D_;
      take(v0);
      next_down(true);
      sa += 2048;
      pace(H_K);
    }
    if (t == 64) prefetch_l2(out + (size_t)bid * 16 * D_, 16 * D_ * 2);
    if (t == 32) wait_out_init(tag);
    named_bar(1, 96);
    {
      uint4 hv[3];
      uint32_t it = 0;
      bool bad[3] = {true, true, w == 0};
      while (true) {
#pragma unroll
        for (int i = 0; i < 3; i++) if (bad[i]) hv[i] = ld_rec2(g_h + kg * 448 + 2 * (t + 96 * i));
#pragma unroll
        for (int i = 0; i < 3; i++) bad[i] = bad[i] && (hv[i].y != tag || hv[i].w != tag);
        if (!poll_again(bad[0] || bad[1] || bad[2], it)) break;
        __nanosleep(100);
      }
#pragma unroll
      for (int i = 0; i < 3; i++) {
        if (t + 96 * i < 224) ((float4*)xs)[t + 96 * i] = make_float4(bf_lo(hv[i].x), bf_hi(hv[i].x), bf_lo(hv[i].z), bf_hi(hv[i].z));
      }
    }
    named_bar(1, 96);
    if (t == 0) TL(10);
    {
      float ay[16];
#pragma unroll
      for (int q = 0; q < 16; q++) ay[q] = 0.f;
      const float2* hp = xs + 16 * w + (lane >> 3);
      xv[0] = hp[0];
      xv[1] = hp[4];
      auto unit = [&](const uint4 (&v)[4], uint4 (&vn)[4], int u) {
        take(vn);
        xv[2] = hp[8];
        xv[3] = hp[12];
        hp += 48;
        half(ay, v, 0);
        xv[0] = hp[0];
        xv[1] = hp[4];
        next_down(u + 5 < ndn);
        sa = ring + ((sa - ring + 2048) & 8191);
        half(ay, v, 1);
      };
#pragma unroll 1
      for (int u = 0; u < ndn; u += 2) {
        unit(v0, v1, u);
        if (u + 1 < ndn) unit(v1, v0, u + 1);
      }
      xreduce<8, 16>(ay, lane);
      xreduce<4, 8>(ay, lane);
      ((float4*)red)[w * 32 + (lane & 7) * 4 + (lane >> 3)] = make_float4(ay[0], ay[1], ay[2], ay[3]);
    }
    named_bar(1, 96);
    if (t < 64) {
      const float* r = red + 4 * lane + w;
      const uint32_t key = misc[2 + w];
      const uint32_t rb = (key ^ (0x80000000u | ~(uint32_t)((int32_t)key >> 31))) & 0xffff0000u;
      const float gate = bf_round(__fdividef(1.f, 1.f + __expf(-__uint_as_float(rb))));
      const uint32_t v = pack_bf16((r[0] + r[128] + r[256]) * gate, (r[2] + r[130] + r[258]) * gate);
      asm volatile("red.relaxed.gpu.global.add.noftz.bf16x2 [%0], %1;"
                   ::"l"(out + (size_t)(S_ - 1 - (key & (S_ - 1))) * D_ + cb * 64 + 2 * lane), "r"(v) : "memory");
      if (t == 0) TL(6);
    }
  } else {
    float acc[128];
    const int wg = warp >> 2, wi = warp & 3;
    const bool elect = (tid & 127) == 0;
    const uint32_t a_base = base + wg * (A_BYTES / 2);

    auto release = [&](int k) {
      if (elect) mbar_arrive(empty0 + 8 * (k & 3));
    };
    auto mma_step = [&](int st, int scale_d) {
      const uint64_t da = make_desc(a_base + st * A_BYTES), db = make_desc(base + OFF_B + st * B_BYTES);
      wgmma_fence();
      wgmma_n256(acc, da, db, scale_d);
      wgmma_n256(acc, da + 2, db + 2, 1);
      wgmma_n256(acc, da + 4, db + 4, 1);
      wgmma_commit();
      wgmma_n256(acc, da + 6, db + 6, 1);
      wgmma_commit();
    };
    auto stamp = [&](int k) {
      if (elect) TK(wg, k);
    };

#pragma unroll 1
    for (int k = 0; k < K1; k++) {
      if (k < CP0) {
        cp_wait<CP0 - 1>();
        asm volatile("cp.async.commit_group;" ::: "memory");
        fence_proxy_async_smem();
        named_bar(4, 256);
        if (tid == 0) mbar_arrive(full0 + 8 * k);
        stamp(k);
      } else {
        stamp(k);
        mbar_wait(full0 + 8 * (k & 3), (k >> 2) & 1);
        TKC(k);
      }
      mma_step(k & 3, k);
      wgmma_wait<2>();
      if (k) release(k - 1);
    }
    {
      mbar_wait(bar_stat, 0);
      uint32_t af[2];
#pragma unroll
      for (int h = 0; h < 2; h++) {
        af[h] = lds32(auxs + OFF_WSUM + (wg * 64 + wi * 16 + h * 8 + (lane >> 2)) * 8 + (lane & 1) * 4);
        if (lane & 2) af[h] = 0;
      }
      wgmma_fence();
      wgmma_n256_rs(acc, af[0], af[1], 0u, 0u, (uint64_t)(((auxs + OFF_MEAN) & 0x3FFFF) >> 4) | ((uint64_t)8 << 32));
      wgmma_commit();
      const uint32_t dst = __shfl_sync(0xffffffffu, a_base + (wi * 16 + (lane & 15)) * 128 + (((lane >> 4) ^ (lane & 7)) << 4), lane);
      const uint32_t cst = auxs + OFF_COLSTAT + (lane & 3) * 16;
      uint4 cn[8];
#pragma unroll
      for (int p = 0; p < 4; p++) cn[p] = lds128(cst + p * 64);
      mbar_wait(full0, 0);
      wgmma_wait<1>();
      release(K1 - 1);
      wgmma_wait<0>();
      if (elect) TL(12 + wg);
#pragma unroll
      for (int p = 0; p < 16; p++) {
        const uint32_t c0 = p & 1 ? cn[p >> 1].z : cn[p >> 1].x, c1 = p & 1 ? cn[p >> 1].w : cn[p >> 1].y;
        const float4 c = make_float4(bf_lo(c0), __uint_as_float(c0), bf_lo(c1), __uint_as_float(c1));
        stmatrix_x4((dst ^ ((p & 3) << 5)) + (p >> 2) * A_BYTES, pack_bf16(acc[8 * p] * c.x, acc[8 * p + 1] * c.y),
                    pack_bf16(acc[8 * p + 2] * c.x, acc[8 * p + 3] * c.y), pack_bf16(acc[8 * p + 4] * c.z, acc[8 * p + 5] * c.w),
                    pack_bf16(acc[8 * p + 6] * c.z, acc[8 * p + 7] * c.w));
        if (p == 3 || p == 15) {
          if (p == 3) fence_proxy_async_smem();
          __syncwarp();
          if (lane == 0) mbar_arrive(bar_ab + 16 * wg + (p & 8));
        }
        if (p == 3) {
#pragma unroll
          for (int q = 4; q < 8; q++) cn[q] = lds128(cst + q * 64);
        }
      }
      named_bar(2 + wg, 128);
      if (elect) TL(29 + wg);
    }
#pragma unroll
    for (int i = 0; i < 128; i++) asm volatile("" : "=f"(acc[i]));
    stamp(K1);
    mma_step(0, 0);
    mbar_wait(bar_ab + 16 * wg + 8, 0);
    fence_proxy_async_smem();
#pragma unroll 1
    for (int k = K1 + 1; k < KT - 4; k++) {
      const bool early = k == K1 + 4;
      if (early) {
        wgmma_wait<0>();
        release(k - 1);
      }
      stamp(k);
      mbar_wait(full0 + 8 * (k & 3), (k >> 2) & 1);
      TKC(k);
      mma_step(k & 3, 1);
      wgmma_wait<2>();
      if (!early) release(k - 1);
    }
    const bool second = wg != FW;
    auto turn = [&](auto oc, int i, uint32_t a, int hs) {
      const uint64_t da = make_desc(a), db = make_desc(base + OFF_B + hs * (B_BYTES / 2));
      wgmma_fence();
#pragma unroll
      for (int q = 0; q < 4; q++) wgmma_n128<decltype(oc)::value>(acc, da + 2 * q, db + 2 * q);
      wgmma_commit();
    };
    const uint32_t a3 = base + OFF_B + 3 * (B_BYTES / 2) + wg * (A_BYTES / 2);
    const uint32_t o0 = ((lane >> 4) * 8 + (lane & 7)) * 128 + (((2 * wi + ((lane >> 3) & 1)) ^ (lane & 7)) << 4);
    auto send = [&](auto oc, uint32_t dst, uint32_t pitch) {
      constexpr int O = decltype(oc)::value;
#pragma unroll
      for (int h = 0; h < 2; h++) {
#pragma unroll
        for (int p = 0; p < 4; p++) {
          const float* v = acc + O + 32 * h + 8 * p;
          stmatrix_x4_t(dst + h * pitch + o0 + p * 2048, pack_bf16(v[0], v[1]), pack_bf16(v[2], v[3]), pack_bf16(v[4], v[5]), pack_bf16(v[6], v[7]));
        }
        fence_proxy_async_smem();
        named_bar(2 + wg, 128);
        if (elect) {
          tma_red_add(&maps.out, dst + h * pitch, eb * 128 + wg * 64, (j * 4 + O / 32 + h) * (PR / 4));
          if (h == 0) TL(24 + (O / 32) + second + 9);
        }
        __syncwarp();
      }
    };
    const uint32_t zero = __shfl_sync(0xffffffffu, lds32(kcur) >> 8, 0);
    auto cut = [&](int lo, int hi) {
      if (CUTOP == 2) {
        if (zero) {
#pragma unroll
          for (int i = lo; i < hi; i++) acc[i] *= __uint_as_float(zero);
        }
      }
      if (CUTOP == 3) {
#pragma unroll 1
        for (uint32_t r = 0; r < zero; r++) {
#pragma unroll
          for (int i = lo; i < hi; i++) acc[i] *= __uint_as_float(zero);
        }
      }
#pragma unroll
      for (int i = lo; i < hi; i++) {
        if (CUTOP == 0) acc[i] = __uint_as_float(__float_as_uint(acc[i]) ^ zero);
        if (CUTOP == 1) acc[i] *= __uint_as_float(zero | 0x3f800000u);
      }
    };
    mbar_wait(full0, 1);
    wgmma_wait<0>();
    release(KT - 5);
    if (CUT == 1 || CUT == 3) cut(0, 64);
    if (CUT == 2) cut(0, 128);
    if (CUT == 4) cut(64, 128);
    if (second) {
      mbar_wait(full0 + 8, 1);
      mbar_wait(full0 + 16, 1);
      named_bar(4, 256);
    }
    stamp(KT - 4);
    turn(IC<0>{}, 0, a_base, 0);
    if (!second) mbar_wait(full0 + 8, 1);
    turn(IC<0>{}, 1, a_base + A_BYTES, 2);
    if (!second) mbar_wait(full0 + 16, 1);
    turn(IC<0>{}, 2, a_base + 2 * A_BYTES, 4);
    wgmma_wait<2>();
    release(0);
    turn(IC<0>{}, 3, a3, 5);
    named_arrive(4 + second, 256);
    stamp(KT - 3);
    if (elect) {
      mbar_wait(bar_out + 8, 0);
      fence_proxy_async();
    }
    __syncwarp();
    mbar_wait(second ? bar_out : empty0 + 24, 0);
    wgmma_wait<2>();
    if (second) named_bar(2 + wg, 128);
    wgmma_wait<0>();
    if (elect && !second) mbar_arrive(bar_out);
    if (elect) TL(24 + second);
    send(IC<0>{}, second ? base + OFF_B + B_BYTES : base + 3 * A_BYTES, A_BYTES / 2);
    if (CUT == 1 || CUT == 5) cut(64, 128);
    mbar_wait(full0 + 24, 1);
    if (second) mbar_wait(full0, 0);
    named_bar(5 + second, 256);
    stamp(KT - 2);
    turn(IC<64>{}, 0, a_base, 1);
    turn(IC<64>{}, 1, a_base + A_BYTES, 6);
    turn(IC<64>{}, 2, a_base + 2 * A_BYTES, 7);
    if (!second) mbar_wait(full0, 0);
    turn(IC<64>{}, 3, a3, 0);
    if (!second) named_arrive(6, 256);
    stamp(KT - 1);
    wgmma_wait<2>();
    named_bar(2 + wg, 128);
    wgmma_wait<0>();
    if (elect) TL(20 + second);
    send(IC<64>{}, a_base, A_BYTES);
    if (elect) {
      bulk_commit();
      bulk_wait_read<0>();
      if (second) TL(18);
    }
  }
}

typedef CUresult (*EncodeFn)(CUtensorMap*, CUtensorMapDataType, cuuint32_t, void*, const cuuint64_t*, const cuuint64_t*, const cuuint32_t*,
                             const cuuint32_t*, CUtensorMapInterleave, CUtensorMapSwizzle, CUtensorMapL2promotion, CUtensorMapFloatOOBfill);

void make_map(EncodeFn enc, CUtensorMap* m, void* ptr, uint64_t rows, uint64_t cols, uint32_t box_rows, CUtensorMapL2promotion promo,
              uint32_t box_cols = 64, CUtensorMapSwizzle sw = CU_TENSOR_MAP_SWIZZLE_128B) {
  cuuint64_t dims[2] = {cols, rows};
  cuuint64_t strides[1] = {cols * 2};
  cuuint32_t box[2] = {box_cols, box_rows};
  cuuint32_t es[2] = {1, 1};
  enc(m, CU_TENSOR_MAP_DATA_TYPE_BFLOAT16, 2, ptr, dims, strides, box, es, CU_TENSOR_MAP_INTERLEAVE_NONE, sw, promo,
      CU_TENSOR_MAP_FLOAT_OOB_FILL_NONE);
}

void make_map5(EncodeFn enc, CUtensorMap* m, void* ptr, uint64_t cols, uint32_t box_rows, uint32_t box_cols, CUtensorMapSwizzle sw) {
  cuuint64_t dims[5] = {cols, 2, 2, PG, 512 / PG};
  cuuint64_t strides[4] = {cols * 2 * 1024, cols * 2 * 512, cols * 2 * (512 / PG), cols * 2};
  cuuint32_t box[5] = {box_cols, 2, 2, PG, box_rows / (4 * PG)};
  cuuint32_t es[5] = {1, 1, 1, 1, 1};
  enc(m, CU_TENSOR_MAP_DATA_TYPE_BFLOAT16, 5, ptr, dims, strides, box, es, CU_TENSOR_MAP_INTERLEAVE_NONE, sw,
      CU_TENSOR_MAP_L2_PROMOTION_L2_128B, CU_TENSOR_MAP_FLOAT_OOB_FILL_NONE);
}

}

extern "C" void kernel_launch(void* const* d_in, const int* in_sizes, int n_in, void* d_out, int out_size) {
  (void)in_sizes; (void)n_in; (void)out_size;
  void* fn = nullptr;
  cudaDriverEntryPointQueryResult qr;
  cudaGetDriverEntryPoint("cuTensorMapEncodeTiled", &fn, cudaEnableDefault, &qr);
  EncodeFn enc = (EncodeFn)fn;
  void* ab = nullptr;
  cudaGetSymbolAddress(&ab, g_ab);
  Maps maps;
  const CUtensorMapL2promotion P256 = CU_TENSOR_MAP_L2_PROMOTION_L2_256B, P128 = CU_TENSOR_MAP_L2_PROMOTION_L2_128B;
  make_map(enc, &maps.x, d_in[0], S_, D_, 256, P256);
  for (int p = 0; p < 2; p++) {
    make_map5(enc, &maps.ws[p], d_in[1 + p], S_, 256, 64, CU_TENSOR_MAP_SWIZZLE_128B);
    make_map5(enc, &maps.ws_h[p], d_in[1 + p], S_, 128, 64, CU_TENSOR_MAP_SWIZZLE_128B);
    make_map5(enc, &maps.ws_pf[p], d_in[1 + p], S_, 32, 128, CU_TENSOR_MAP_SWIZZLE_NONE);
  }
  make_map(enc, &maps.wd[0], d_in[3], D_, D_, 128, P256);
  make_map(enc, &maps.wd[1], d_in[4], D_, D_, 128, P256);
  make_map(enc, &maps.ab_ld, ab, 2 * D_, S_, 128, P128);
  make_map(enc, &maps.ab_st, ab, 2 * D_, S_, 64, P128);
  make_map5(enc, &maps.out, d_out, D_, 64, 64, CU_TENSOR_MAP_SWIZZLE_128B);
  cudaFuncSetAttribute(fused_kernel, cudaFuncAttributeMaxDynamicSharedMemorySize, SMEM_BYTES);
  fused_kernel<<<NCTA, 384,
      SMEM_BYTES, cudaStreamPerThread>>>(
      (const __nv_bfloat16*)d_in[0], (const __nv_bfloat16*)d_in[3], (const __nv_bfloat16*)d_in[4], (const __nv_bfloat16*)d_in[6],
      (const __nv_bfloat16*)d_in[7], (const __nv_bfloat16*)d_in[8], maps, (const __nv_bfloat16*)d_in[9], (__nv_bfloat16*)d_out);
}
```

```cpp
#include <cuda_runtime.h>
#include <cuda_bf16.h>
#include <cuda.h>
#include <stdint.h>

#define DEVI __device__ __forceinline__

namespace {

constexpr int S_ = 2048, D_ = 1024, F_ = 3584;
constexpr int STAGES = 4;
constexpr int A_BYTES = 128 * 64 * 2, B_BYTES = 256 * 64 * 2;
constexpr int K1 = 16, K2 = 32, KT = K1 + K2;
constexpr int NCTA = 128;
constexpr int NFFN = 112;
constexpr int PG = 4;
constexpr int PR = 64 / PG;
constexpr int NMIR = 4;
constexpr int NB0 = 8;
constexpr int LN_K0 = 4;
constexpr int GU_KF = 15;
constexpr int GU_K1 = 22;
constexpr int GU_K0 = 24;
constexpr int H_K = 30;
constexpr unsigned long long WS_MASK = 0x1a0000fff80ull;

constexpr int OFF_B = STAGES * A_BYTES;
constexpr int OFF_AUX = OFF_B + STAGES * B_BYTES;
constexpr int OFF_RING = 0;
constexpr int OFF_XS = OFF_RING + 3 * 8192;
constexpr int OFF_GU = OFF_XS + 4096;
constexpr int OFF_MEAN = OFF_GU;
constexpr int OFF_COLSTAT = OFF_XS + 8192;
constexpr int OFF_RED = OFF_COLSTAT;
constexpr int OFF_WSUM = OFF_COLSTAT + 512;
constexpr int OFF_FLAGS = OFF_COLSTAT + 1536;
constexpr int OFF_BAR = OFF_COLSTAT + 2048;
constexpr int OFF_MISC = OFF_BAR + 224;
constexpr int AUX_BYTES = OFF_MISC + 32;
constexpr int SMEM_BYTES = OFF_AUX + AUX_BYTES;
static_assert(SMEM_BYTES <= 232448, "smem");

template <int V> struct IC { static constexpr int value = V; };

struct Maps {
  CUtensorMap x, wd[2], ws[2], ws_h[2], ws_pf[2], ab_ld, ab_st, out;
};

__device__ __nv_bfloat16 g_ab[2 * D_ * S_];
__device__ uint2 g_stat[S_];
__device__ uint2 g_wsum[2 * D_];
__device__ uint2 g_cand[NCTA * 3];
__device__ uint2 g_h[F_];
__device__ __align__(128) uint32_t g_abflag[16 * 3 * 32];
__device__ uint32_t g_ctr;
#define TL(i) do {} while (0)
#define TK(r, k) do {} while (0)

#define TKP(r, k) TK(r, k)
#define TKC(k)
DEVI uint32_t smem_u32(const void* p) { return (uint32_t)__cvta_generic_to_shared(p); }
DEVI void mbar_init(uint32_t bar, uint32_t cnt) { asm volatile("mbarrier.init.shared::cta.b64 [%0], %1;" ::"r"(bar), "r"(cnt) : "memory"); }
DEVI void mbar_expect_tx(uint32_t bar, uint32_t bytes) { asm volatile("mbarrier.arrive.expect_tx.shared::cta.b64 _, [%0], %1;" ::"r"(bar), "r"(bytes) : "memory"); }
DEVI void mbar_arrive(uint32_t bar) { asm volatile("mbarrier.arrive.shared::cta.b64 _, [%0];" ::"r"(bar) : "memory"); }
DEVI void mbar_arrive_cluster(uint32_t bar, uint32_t cta) {
  asm volatile("{\n.reg .b32 ra;\nmapa.shared::cluster.u32 ra, %0, %1;\nmbarrier.arrive.shared::cluster.b64 _, [ra];\n}" ::"r"(bar), "r"(cta) : "memory");
}
DEVI uint32_t mapa(uint32_t a, uint32_t cta) { uint32_t r; asm("mapa.shared::cluster.u32 %0, %1, %2;" : "=r"(r) : "r"(a), "r"(cta)); return r; }
DEVI void st_async4(uint32_t dst, float a, float b, float c, float d, uint32_t bar) {
  asm volatile("st.async.shared::cluster.mbarrier::complete_tx::bytes.v4.f32 [%0], {%1, %2, %3, %4}, [%5];"
               ::"r"(dst), "f"(a), "f"(b), "f"(c), "f"(d), "r"(bar) : "memory");
}
DEVI bool mbar_try_wait(uint32_t bar, uint32_t parity) {
  uint32_t ok;
  asm volatile("{\n.reg .pred p;\nmbarrier.try_wait.parity.shared::cta.b64 p, [%1], %2;\nselp.u32 %0, 1, 0, p;\n}" : "=r"(ok) : "r"(bar), "r"(parity) : "memory");
  return ok;
}
DEVI bool mbar_test(uint32_t bar, uint32_t parity) {
  uint32_t ok;
  asm volatile("{\n.reg .pred p;\nmbarrier.test_wait.parity.shared::cta.b64 p, [%1], %2;\nselp.u32 %0, 1, 0, p;\n}" : "=r"(ok) : "r"(bar), "r"(parity) : "memory");
  return ok;
}
DEVI void mbar_wait(uint32_t bar, uint32_t parity) {
  uint32_t n = 0;
  while (!mbar_try_wait(bar, parity)) { if (++n > (1u << 20)) __trap(); }
}
DEVI void tma_load(uint32_t dst, const CUtensorMap* m, int c0, int c1, uint32_t bar) {
  asm volatile("cp.async.bulk.tensor.2d.shared::cluster.global.mbarrier::complete_tx::bytes [%0], [%1, {%3, %4}], [%2];"
               ::"r"(dst), "l"(m), "r"(bar), "r"(c0), "r"(c1) : "memory");
}
DEVI void tma_load5(uint32_t dst, const CUtensorMap* m, int c0, int c4, uint32_t bar) {
  asm volatile("cp.async.bulk.tensor.5d.shared::cluster.global.mbarrier::complete_tx::bytes [%0], [%1, {%3, %5, %5, %5, %4}], [%2];"
               ::"r"(dst), "l"(m), "r"(bar), "r"(c0), "r"(c4), "r"(0) : "memory");
}
DEVI void tma_store(const CUtensorMap* m, uint32_t src, int c0, int c1) {
  asm volatile("cp.async.bulk.tensor.2d.global.shared::cta.bulk_group [%0, {%2, %3}], [%1];" ::"l"(m), "r"(src), "r"(c0), "r"(c1) : "memory");
}
DEVI void tma_red_add(const CUtensorMap* m, uint32_t src, int c0, int c1) {
  asm volatile("cp.reduce.async.bulk.tensor.5d.global.shared::cta.add.bulk_group [%0, {%2, %4, %4, %4, %3}], [%1];" ::"l"(m), "r"(src), "r"(c0), "r"(c1), "r"(0) : "memory");
}
DEVI uint4 lds128(uint32_t a) { uint4 v; asm volatile("ld.shared.v4.u32 {%0,%1,%2,%3}, [%4];" : "=r"(v.x), "=r"(v.y), "=r"(v.z), "=r"(v.w) : "r"(a) : "memory"); return v; }
DEVI uint32_t lds32(uint32_t a) { uint32_t v; asm volatile("ld.volatile.shared.u32 %0, [%1];" : "=r"(v) : "r"(a) : "memory"); return v; }
DEVI void sts32(uint32_t a, uint32_t v) { asm volatile("st.volatile.shared.u32 [%0], %1;" ::"r"(a), "r"(v) : "memory"); }
DEVI void tma_prefetch(const CUtensorMap* m, int c0, int c1) {
  asm volatile("cp.async.bulk.prefetch.tensor.5d.L2.global [%0, {%1, %3, %3, %3, %2}];" ::"l"(m), "r"(c0), "r"(c1), "r"(0) : "memory");
}
DEVI void cp_async16(uint32_t dst, const void* src) { asm volatile("cp.async.cg.shared.global [%0], [%1], 16;" ::"r"(dst), "l"(src) : "memory"); }
DEVI void cp_async16_once(uint32_t dst, const void* src) {
  asm volatile("{\n.reg .b64 pol;\ncreatepolicy.fractional.L2::evict_first.b64 pol, 1.0;\n"
               "cp.async.cg.shared.global.L2::cache_hint [%0], [%1], 16, pol;\n}" ::"r"(dst), "l"(src) : "memory");
}
DEVI bool elect_one() {
  uint32_t p;
  asm volatile("{\n.reg .pred P;\nelect.sync _|P, 0xffffffff;\nselp.u32 %0, 1, 0, P;\n}" : "=r"(p));
  return p;
}
DEVI float sqrt_approx(float v) { float r; asm("sqrt.approx.ftz.f32 %0, %1;" : "=f"(r) : "f"(v)); return r; }
DEVI float rcp_approx(float v) { float r; asm("rcp.approx.ftz.f32 %0, %1;" : "=f"(r) : "f"(v)); return r; }
DEVI void bulk_commit() { asm volatile("cp.async.bulk.commit_group;" ::: "memory"); }
template <int N> DEVI void bulk_wait() { asm volatile("cp.async.bulk.wait_group %0;" ::"n"(N) : "memory"); }
template <int N> DEVI void bulk_wait_read() { asm volatile("cp.async.bulk.wait_group.read %0;" ::"n"(N) : "memory"); }
DEVI void fence_proxy_async() { asm volatile("fence.proxy.async.global;" ::: "memory"); }
DEVI void fence_proxy_async_smem() { asm volatile("fence.proxy.async.shared::cta;" ::: "memory"); }
DEVI void prefetch_map(const CUtensorMap* m) { asm volatile("prefetch.tensormap [%0];" ::"l"(m) : "memory"); }
DEVI void named_bar(int id, int n) { asm volatile("bar.sync %0, %1;" ::"r"(id), "r"(n) : "memory"); }
DEVI void named_arrive(int id, int n) { asm volatile("bar.arrive %0, %1;" ::"r"(id), "r"(n) : "memory"); }
DEVI void wgmma_fence() { asm volatile("wgmma.fence.sync.aligned;" ::: "memory"); }
DEVI void wgmma_commit() { asm volatile("wgmma.commit_group.sync.aligned;" ::: "memory"); }
template <int N> DEVI void wgmma_wait() { asm volatile("wgmma.wait_group.sync.aligned %0;" ::"n"(N) : "memory"); }
DEVI uint64_t make_desc(uint32_t addr) {
  return (uint64_t)((addr & 0x3FFFF) >> 4) | ((uint64_t)1 << 16) | ((uint64_t)64 << 32) | ((uint64_t)1 << 62);
}
DEVI uint32_t ld_acquire(const uint32_t* p) { uint32_t v; asm volatile("ld.acquire.gpu.global.u32 %0, [%1];" : "=r"(v) : "l"(p) : "memory"); return v; }
DEVI void fence_gpu() { asm volatile("fence.acq_rel.gpu;" ::: "memory"); }
DEVI uint32_t ld_relaxed(const uint32_t* p) { uint32_t v; asm volatile("ld.relaxed.gpu.global.u32 %0, [%1];" : "=r"(v) : "l"(p) : "memory"); return v; }
DEVI void st_rec(uint2* p, uint32_t a, uint32_t b) {
  asm volatile("{\n.reg .b64 t;\nmov.b64 t, {%1, %2};\nst.relaxed.gpu.global.b64 [%0], t;\n}" ::"l"(p), "r"(a), "r"(b) : "memory");
}
DEVI uint4 ld_rec2(const uint2* p) {
  uint4 v;
  asm volatile("{\n.reg .b64 a, b;\nld.relaxed.gpu.global.v2.b64 {a, b}, [%4];\nmov.b64 {%0, %1}, a;\nmov.b64 {%2, %3}, b;\n}"
               : "=r"(v.x), "=r"(v.y), "=r"(v.z), "=r"(v.w) : "l"(p) : "memory");
  return v;
}
DEVI uint2 ld_rec(const uint2* p) {
  uint2 v;
  asm volatile("{\n.reg .b64 a;\nld.relaxed.gpu.global.b64 a, [%2];\nmov.b64 {%0, %1}, a;\n}" : "=r"(v.x), "=r"(v.y) : "l"(p) : "memory");
  return v;
}
DEVI bool poll_again(bool bad, uint32_t& it) {
  if (!__any_sync(0xffffffffu, bad)) return false;
  if (++it > (1u << 18)) __trap();
  __nanosleep(40);
  return true;
}
DEVI void st_relaxed(uint32_t* p, uint32_t v) { asm volatile("st.relaxed.gpu.global.u32 [%0], %1;" ::"l"(p), "r"(v) : "memory"); }
DEVI uint32_t pack_bf16(float lo, float hi) { uint32_t r; asm("cvt.rn.bf16x2.f32 %0, %1, %2;" : "=r"(r) : "f"(hi), "f"(lo)); return r; }
DEVI float bf_lo(uint32_t v) { return __uint_as_float(v << 16); }
DEVI float bf_hi(uint32_t v) { return __uint_as_float(v & 0xffff0000u); }
DEVI float bf_round(float v) { return bf_hi(pack_bf16(0.f, v)); }
DEVI uint32_t bf2_sub(uint32_t a, uint32_t b) { uint32_t r; asm("sub.rn.bf16x2 %0, %1, %2;" : "=r"(r) : "r"(a), "r"(b)); return r; }
DEVI uint32_t bf2_fma(uint32_t a, uint32_t b, uint32_t c) { uint32_t r; asm("fma.rn.bf16x2 %0, %1, %2, %3;" : "=r"(r) : "r"(a), "r"(b), "r"(c)); return r; }
DEVI void prefetch_l2(const void* p, uint32_t bytes) { asm volatile("cp.async.bulk.prefetch.L2.global [%0], %1;" ::"l"(p), "r"(bytes) : "memory"); }
DEVI void stmatrix_x4(uint32_t addr, uint32_t a, uint32_t b, uint32_t c, uint32_t d) {
  asm volatile("stmatrix.sync.aligned.m8n8.x4.shared.b16 [%0], {%1,%2,%3,%4};" ::"r"(addr), "r"(a), "r"(b), "r"(c), "r"(d) : "memory");
}
DEVI void stmatrix_x4_t(uint32_t addr, uint32_t a, uint32_t b, uint32_t c, uint32_t d) {
  asm volatile("stmatrix.sync.aligned.m8n8.x4.trans.shared.b16 [%0], {%1,%2,%3,%4};" ::"r"(addr), "r"(a), "r"(b), "r"(c), "r"(d) : "memory");
}
DEVI void gemv8(float (&acc)[16], const uint4& v, const float2 xv) {
  const uint32_t g4[4] = {v.x, v.y, v.z, v.w};
#pragma unroll
  for (int c = 0; c < 4; c++) {
    const float lo = bf_lo(g4[c]), hi = bf_hi(g4[c]);
    acc[4 * c + 0] = fmaf(lo, xv.x, acc[4 * c + 0]);
    acc[4 * c + 1] = fmaf(lo, xv.y, acc[4 * c + 1]);
    acc[4 * c + 2] = fmaf(hi, xv.x, acc[4 * c + 2]);
    acc[4 * c + 3] = fmaf(hi, xv.y, acc[4 * c + 3]);
  }
}
template <int H, int MASK, int N> DEVI void xreduce(float (&s)[N], int lane) {
  const bool up = lane & MASK;
#pragma unroll
  for (int i = 0; i < H; i++) {
    const float keep = up ? s[i + H] : s[i], send = up ? s[i] : s[i + H];
    s[i] = keep + __shfl_xor_sync(0xffffffffu, send, MASK);
  }
}
DEVI float warp_sum(float v) {
#pragma unroll
  for (int o = 16; o; o >>= 1) v += __shfl_xor_sync(0xffffffffu, v, o);
  return v;
}

#define ACC128 \
      "{%0,%1,%2,%3,%4,%5,%6,%7,%8,%9,%10,%11,%12,%13,%14,%15,%16,%17,%18,%19,%20,%21,%22,%23,%24,%25,%26,%27,%28,%29,%30,%31," \
      "%32,%33,%34,%35,%36,%37,%38,%39,%40,%41,%42,%43,%44,%45,%46,%47,%48,%49,%50,%51,%52,%53,%54,%55,%56,%57,%58,%59,%60,%61,%62,%63," \
      "%64,%65,%66,%67,%68,%69,%70,%71,%72,%73,%74,%75,%76,%77,%78,%79,%80,%81,%82,%83,%84,%85,%86,%87,%88,%89,%90,%91,%92,%93,%94,%95," \
      "%96,%97,%98,%99,%100,%101,%102,%103,%104,%105,%106,%107,%108,%109,%110,%111,%112,%113,%114,%115,%116,%117,%118,%119,%120,%121,%122,%123,%124,%125,%126,%127},"
#define R128(d) R8(d, 0), R8(d, 8), R8(d, 16), R8(d, 24), R8(d, 32), R8(d, 40), R8(d, 48), R8(d, 56), R8(d, 64), R8(d, 72), R8(d, 80), \
                R8(d, 88), R8(d, 96), R8(d, 104), R8(d, 112), R8(d, 120)
#define R8(d, i) "+f"(d[i]), "+f"(d[i + 1]), "+f"(d[i + 2]), "+f"(d[i + 3]), "+f"(d[i + 4]), "+f"(d[i + 5]), "+f"(d[i + 6]), "+f"(d[i + 7])
DEVI void wgmma_n256(float (&d)[128], uint64_t da, uint64_t db, int scale_d) {
  asm volatile("{\n.reg .pred p;\nsetp.ne.b32 p, %130, 0;\nwgmma.mma_async.sync.aligned.m64n256k16.f32.bf16.bf16 " ACC128
               " %128, %129, p, 1, 1, 0, 0;\n}\n" : R128(d) : "l"(da), "l"(db), "r"(scale_d));
}
DEVI void wgmma_n256_rs(float (&d)[128], uint32_t a0, uint32_t a1, uint32_t a2, uint32_t a3, uint64_t db) {
  asm volatile("wgmma.mma_async.sync.aligned.m64n256k16.f32.bf16.bf16 " ACC128 " {%128, %129, %130, %131}, %132, 1, 1, 1, 0;\n"
               : R128(d) : "r"(a0), "r"(a1), "r"(a2), "r"(a3), "l"(db));
}

#define ACC64 \
      "{%0,%1,%2,%3,%4,%5,%6,%7,%8,%9,%10,%11,%12,%13,%14,%15,%16,%17,%18,%19,%20,%21,%22,%23,%24,%25,%26,%27,%28,%29,%30,%31," \
      "%32,%33,%34,%35,%36,%37,%38,%39,%40,%41,%42,%43,%44,%45,%46,%47,%48,%49,%50,%51,%52,%53,%54,%55,%56,%57,%58,%59,%60,%61,%62,%63},"
template <int O> DEVI void wgmma_n128(float (&d)[128], uint64_t da, uint64_t db) {
  asm volatile("wgmma.mma_async.sync.aligned.m64n128k16.f32.bf16.bf16 " ACC64 " %64, %65, 1, 1, 1, 0, 0;\n"
               : R8(d, O), R8(d, O + 8), R8(d, O + 16), R8(d, O + 24), R8(d, O + 32), R8(d, O + 40), R8(d, O + 48), R8(d, O + 56)
               : "l"(da), "l"(db));
}

DEVI void wait_out_init(uint32_t tag) {
  uint32_t it = 0;
  while ((int32_t)(ld_acquire(&g_ctr) - tag) < 0) { if (++it > (1u << 20)) __trap(); }
}
template <int N> DEVI void cp_wait() { asm volatile("cp.async.wait_group %0;" ::"n"(N) : "memory"); }

DEVI int other_chunk(int m, int j) { return m + (m >= j); }
DEVI int p2_col(int n, int j) {
  const int m = n < 11 ? n - 4 : n < 18 ? n - 11 : (n - 18) >> 1;
  const int slab = n < 11 ? 0 : n < 18 ? 1 : 2 + (n & 1);
  return other_chunk(m, j) * 256 + slab * 64;
}

__global__ void __cluster_dims__(2, 1, 1) __launch_bounds__(384, 1)
fused_kernel(const __nv_bfloat16* __restrict__ x, const __nv_bfloat16* __restrict__ wd_re, const __nv_bfloat16* __restrict__ wd_im,
             const __nv_bfloat16* __restrict__ w_r, const __nv_bfloat16* __restrict__ w_gate, const __nv_bfloat16* __restrict__ w_up,
             const __grid_constant__ Maps maps, const __nv_bfloat16* __restrict__ w_down, __nv_bfloat16* __restrict__ out) {
  extern __shared__ __align__(1024) uint8_t smem[];
  const uint32_t rank = blockIdx.x & 1;
  const uint32_t base = smem_u32(smem);
  uint8_t* aux = smem + OFF_AUX;
  const uint32_t auxs = base + OFF_AUX;
  const uint32_t full0 = auxs + OFF_BAR, empty0 = full0 + 8 * STAGES, bar_stat = empty0 + 8 * STAGES, bar_ab = bar_stat + 8,
                 bar_out = bar_ab + 32, bar_pub = bar_out + 64, bar_gu = bar_pub + 16;
  const uint32_t kcur = auxs + OFF_MISC + 16;

  const int tid = threadIdx.x, lane = tid & 31;
  if (tid == 256) TL(0);
  const int cl = blockIdx.x >> 1;
  const int pos = cl - 4 + max(((cl - 29) * 37) >> 8, 0) + ((cl - 4) >> 31 & (7 * cl + 36));
  const int j = (~pos & 3) * 2 + (pos >> 5), part = (pos >> 2) & 1, eb = (((pos >> 3) + (pos >> 5)) & 3) * 2 + rank;
  {
    const uint32_t dst = base + (tid >> 3) * 128 + (((tid ^ (tid >> 3)) & 7) << 4);
    const uint32_t off = (tid >> 3) * (D_ * 2) + (tid & 7) * 16;
    const char* pb = (const char*)x + (off + (uint32_t)j * (256 * D_ * 2));
    const char* pa = (const char*)(part ? wd_im : wd_re) + (off + (uint32_t)eb * (128 * D_ * 2));
    if (tid < 256) {
#pragma unroll
      for (int q = 0; q < 12; q++)
        cp_async16(dst + (q < 8 ? OFF_B + q * 4096 : (q - 8) * 4096), q < 8 ? pb + q * (32 * D_ * 2) : pa + (q - 8) * (32 * D_ * 2));
      asm volatile("cp.async.commit_group;" ::: "memory");
    }
    if (tid == 0) TL(15);
  }
  const int warp = __shfl_sync(0xffffffffu, tid >> 5, 0);
  const int bid = j * 16 + part * 8 + eb;
  const __nv_bfloat16* wd_rows = (bid < 64 ? wd_re : wd_im) + (size_t)(bid & 63) * 16 * D_;
  if (warp == 9) ((uint4*)(aux + OFF_FLAGS))[lane] = make_uint4(0, 0, 0, 0);
  if (tid == 256) {
    prefetch_map(&maps.x);
    prefetch_map(&maps.wd[part]);
    if (base & 1023) __trap();
#pragma unroll
    for (int s = 0; s < STAGES; s++) { mbar_init(full0 + 8 * s, 1); mbar_init(empty0 + 8 * s, 2); }
    mbar_init(bar_stat, 1);
#pragma unroll
    for (int s = 0; s < 4; s++) mbar_init(bar_ab + 8 * s, 4);
    mbar_init(bar_pub, 1);
    mbar_init(bar_pub + 8, 2);
    mbar_init(bar_gu, 1);
    mbar_init(bar_pub + 24, 1);
    sts32(kcur, 0);
    mbar_init(bar_out, 1);
    mbar_init(bar_out + 8, 1);
    asm volatile("fence.mbarrier_init.release.cluster;" ::: "memory");
  }
  __syncthreads();
  asm volatile("barrier.cluster.arrive.relaxed.aligned;" ::: "memory");
  asm volatile("barrier.cluster.wait.acquire.aligned;" ::: "memory");

  if (warp == 8) {
    if (elect_one()) {
      const int arow = eb * 128;
      int pf_i = 0;
      auto prefetch_ws = [&](int k) {
        if ((WS_MASK >> k) & 1) {
          tma_prefetch(&maps.ws_pf[part], pf_i < 2 ? j * 256 + pf_i * 128 : pf_i < 9 ? other_chunk(pf_i - 2, j) * 256 : other_chunk(pf_i - 9, j) * 256 + 128,
                       (j * 8 + eb) * (PR / 8));
          pf_i++;
        }
      };
      auto load_b = [&](int st, const CUtensorMap* m, int col) { tma_load5(base + OFF_B + st * B_BYTES, m, col, j * PR, full0 + 8 * st); };
      TL(1);
#pragma unroll 1
      for (int k = 1; k < K1 + 3; k++) {
        const int st = k & 3;
        mbar_wait(empty0 + 8 * st, ((k >> 2) & 1) ^ 1);
        TKP(2, k);
        if (k < K1) {
          mbar_expect_tx(full0 + 8 * st, A_BYTES + B_BYTES);
          tma_load(base + OFF_B + st * B_BYTES, &maps.x, k * 64, j * 256, full0 + 8 * st);
          tma_load(base + st * A_BYTES, &maps.wd[part], k * 64, arow, full0 + 8 * st);
        } else {
          mbar_expect_tx(full0 + 8 * st, B_BYTES);
          load_b(st, &maps.ws[part], j * 256 + (k - K1) * 64);
        }
        sts32(kcur, k);
        if (k == 4) { prefetch_l2(wd_rows, 16 * D_ * 2); prefetch_map(&maps.ws[part]); prefetch_map(&maps.ws_pf[part]); prefetch_map(&maps.ab_ld); prefetch_map(&maps.ab_st); }
        prefetch_ws(k);
      }
      mbar_wait(bar_stat, 0);
      const uint32_t tag = lds32(auxs + OFF_MISC);
      uint32_t* flags = g_abflag + (eb * 2 + part) * 96;
      mbar_wait(empty0 + 24, 1);
      sts32(kcur, K1 + 3);
      auto put = [&](int h) {
        tma_store(&maps.ab_st, base + h * (A_BYTES / 2), j * 256 + (h >> 1) * 64, part * 1024 + arow + (h & 1) * 64);
        bulk_commit();
      };
#pragma unroll
      for (int w = 1; w >= 0; w--) {
        mbar_wait(bar_ab + 16 * w, 0);
        put(w);
      }
      TL(8);
      TKP(2, K1 + 3);
      mbar_expect_tx(full0 + 24, B_BYTES);
      load_b(3, &maps.ws[part], j * 256 + 192);
      prefetch_ws(K1 + 3);
      bulk_wait<0>();
      TL(11);
      mbar_arrive(bar_pub + 24);
      const uint32_t mirror = auxs + OFF_FLAGS;
      uint32_t mc = 0;
      auto refresh = [&](int col) {
        const int lv = min((col >> 6) & 3, 2);
        cp_async16(mirror + mc + lv * 32, flags + lv * 32);
        cp_async16(mirror + mc + lv * 32 + 16, flags + lv * 32 + 4);
        mc = (mc + 128) & (NMIR * 128 - 1);
      };
      auto ready = [&](int col) {
        const uint32_t a = mirror + min((col >> 6) & 3, 2) * 32 + (col >> 8) * 4;
        uint32_t v[NMIR];
#pragma unroll
        for (int i = 0; i < NMIR; i++) v[i] = lds32(a + i * 128);
        bool r = false;
#pragma unroll
        for (int i = 0; i < NMIR; i++) r |= v[i] == tag;
        return r;
      };
      mbar_wait(bar_ab + 8, 0);
      mbar_wait(bar_ab + 24, 0);
      fence_proxy_async_smem();
      refresh(0);
      {
        uint32_t it = 0;
        while (!mbar_test(empty0, 0)) {
          __nanosleep(150);
          refresh(0);
          if (++it > (1u << 20)) __trap();
        }
      }
      uint32_t seen = 0;
      bool ahead = false;
      auto issue_b = [&](int n) {
        TKP(2, K1 + n);
        mbar_expect_tx(full0 + 8 * (n & 3), A_BYTES + B_BYTES);
        load_b(n & 3, &maps.ws[part], p2_col(n, j));
      };
      auto try_ahead = [&](int n) {
        if (n < 7 && !ahead && mbar_test(empty0 + 8 * (n - 3), 0)) { issue_b(n + 1); ahead = true; }
      };
#pragma unroll 1
      for (int n = 4; n < K2 - 3; n++) {
        const int k = K1 + n, st = k & 3;
        const int col = p2_col(n, j);
        if (!ahead) {
          mbar_wait(empty0 + 8 * st, ((k >> 2) & 1) ^ 1);
          issue_b(n);
        }
        ahead = false;
        if (n == 4) put(4);
        uint32_t it = 3;
        while (!(seen & 1) && !ready(col)) {
          if ((++it & 3) == 0) refresh(col);
          if (it > (1u << 22)) __trap();
          try_ahead(n);
        }
        if (n == 5) mbar_wait(bar_pub, 0);
        if (n == 6) bulk_wait_read<1>();
        if (n == 7) { bulk_wait<0>(); mbar_arrive(bar_pub + 8); TL(23); }
        TKP(3, k);
        tma_load(base + st * A_BYTES, &maps.ab_ld, col, part * 1024 + arow, full0 + 8 * st);
        try_ahead(n);
        if (n < 7) put(n + 1);
        sts32(kcur, k);
        const int col2 = p2_col(n + 2, j);
        seen >>= 1;
        if (ready(col2)) seen |= 2;
        else refresh(col2);
        prefetch_ws(k);
        if (n == 20) { prefetch_map(&maps.ws_h[part]); prefetch_map(&maps.out); }
      }
      const int c1 = p2_col(K2 - 3, j), c2 = p2_col(K2 - 2, j), c3 = c2 + 64;
      auto load_h = [&](int hs, int col, int half, int st) {
        tma_load5(base + OFF_B + hs * (B_BYTES / 2), &maps.ws_h[part], col, j * PR + half * (PR / 2), full0 + 8 * st);
      };
      auto load_a = [&](uint32_t dst, int col, int st) { tma_load(dst, &maps.ab_ld, col, part * 1024 + arow, full0 + 8 * st); };
      {
        uint32_t it = 0;
        while (!(seen & 2) && !ready(c2)) {
          refresh(c2);
          if (++it > (1u << 20)) __trap();
          __nanosleep(200);
        }
      }
      mbar_wait(empty0 + 8, 0);
      TKP(2, KT - 3);
      mbar_expect_tx(full0 + 8, A_BYTES + B_BYTES);
      load_h(2, c1, 0, 1);
      load_a(base + A_BYTES, c1, 1);
      load_a(base + OFF_B + 3 * (B_BYTES / 2), c3, 1);
      sts32(kcur, KT - 3);
      wait_out_init(tag);
      mbar_arrive(bar_out + 8);
      mbar_wait(empty0 + 16, 0);
      TKP(2, KT - 2);
      mbar_expect_tx(full0 + 16, A_BYTES + B_BYTES);
      load_h(4, c2, 0, 2);
      load_a(base + 2 * A_BYTES, c2, 2);
      load_h(5, c3, 0, 2);
      mbar_wait(empty0 + 24, 0);
      TKP(2, KT - 1);
      mbar_expect_tx(full0 + 24, B_BYTES);
      load_h(6, c1, 1, 3);
      load_h(7, c2, 1, 3);
      mbar_wait(empty0, 1);
      TL(17);
      mbar_expect_tx(full0, B_BYTES / 2);
      load_h(0, c3, 1, 0);
      asm volatile("cp.async.wait_all;" ::: "memory");
    }
  } else if (warp > 8) {
    const int t = tid - 288, w = warp - 9;
    float2* xs = (float2*)(aux + OFF_XS);
    float* red = (float*)(aux + OFF_RED);
    volatile uint32_t* misc = (volatile uint32_t*)(aux + OFF_MISC);

    const uint32_t ring = auxs + OFF_RING + (t >> 5) * 8192 + lane * 16;
    auto fetch_to = [&](uint32_t dst, const __nv_bfloat16* src, auto stepc, bool on) {
      if (on) {
#pragma unroll
        for (int k = 0; k < 4; k++) {
          if (decltype(stepc)::value == 256) cp_async16(dst + k * 512, src + k * 256);
          else cp_async16_once(dst + k * 512, src + k * decltype(stepc)::value);
        }
      }
      asm volatile("cp.async.commit_group;" ::: "memory");
    };
    auto fetch = [&](int slot, const __nv_bfloat16* src, auto stepc, bool on) { fetch_to(ring + slot * 2048, src, stepc, on); };
    const int nrow = w ? 5 : 6, lrow0 = w ? 1 + 5 * w : 0;
    const int row0 = bid * 16 + lrow0;
    const __nv_bfloat16* xrow = x + (size_t)row0 * D_ + lane * 8;
    const __nv_bfloat16* wrow = wd_rows + lrow0 * D_ + lane * 8;
    const int slot4 = (OFF_XS - OFF_RING) / 2048 - 4 * w + (w ? w - 1 : 2);
    auto pace = [&](int k) {
      uint32_t it = 0;
      while ((int)lds32(kcur) < k) {
        if (++it > (1u << 20)) __trap();
        __nanosleep(50);
      }
    };
    auto fetch_row = [&](const __nv_bfloat16* p, int i) { fetch(i < 4 ? i : slot4 + i - 4, p + i * D_, IC<256>{}, i < nrow); };
    auto load_row = [&](int i, uint32_t (&xv)[16]) {
      const uint32_t a = ring + (i < 4 ? i : slot4 + i - 4) * 2048;
#pragma unroll
      for (int k = 0; k < 4; k++) {
        const uint4 v = lds128(a + k * 512);
        xv[4 * k] = v.x; xv[4 * k + 1] = v.y; xv[4 * k + 2] = v.z; xv[4 * k + 3] = v.w;
      }
    };
    mbar_wait(full0, 0);
#pragma unroll
    for (int i = 0; i < 3; i++) fetch_row(xrow, i);
    const uint32_t tag = (ld_relaxed(&g_ctr) & ~(uint32_t)(NCTA - 1)) + NCTA;
    const uint32_t tag16 = (tag >> 7) & 0xffffu, tag5 = (tag16 & 31u) << 11;
    uint32_t xo[6][16];
    auto store_row = [&](int i) {
#pragma unroll
      for (int k = 0; k < 4; k++)
        *(uint4*)(out + (size_t)(row0 + i) * D_ + lane * 8 + k * 256) = make_uint4(xo[i][4 * k], xo[i][4 * k + 1], xo[i][4 * k + 2], xo[i][4 * k + 3]);
    };
    {
      uint4 wv4[4];
#pragma unroll
      for (int k = 0; k < 4; k++) wv4[k] = __ldg((const uint4*)(w_r + lane * 8 + k * 256));
      float sh[8];
      const int ri = nrow - 1 - (lane & 7);
      float wr[32];
      float wrsum = 0.f;
#pragma unroll
      for (int k = 0; k < 4; k++) {
        const uint32_t wv[4] = {wv4[k].x, wv4[k].y, wv4[k].z, wv4[k].w};
#pragma unroll
        for (int c = 0; c < 4; c++) {
          wr[8 * k + 2 * c] = bf_lo(wv[c]);
          wr[8 * k + 2 * c + 1] = bf_hi(wv[c]);
          wrsum += wr[8 * k + 2 * c] + wr[8 * k + 2 * c + 1];
        }
      }
      wrsum = warp_sum(wrsum);
#pragma unroll
      for (int q = 0; q < 8; q++) sh[q] = 0.f;
#pragma unroll 1
      for (int i = 0; i < nrow; i++) {
        uint32_t xv[16];
        if (i + 3 < nrow) pace(LN_K0 + i);
        fetch_row(xrow, i + 3);
        cp_wait<3>();
        load_row(i, xv);
        float s0 = 0.f, s1 = 0.f, q0 = 0.f, q1 = 0.f, r0 = 0.f, r1 = 0.f;
#pragma unroll
        for (int c = 0; c < 16; c++) {
          const float a = bf_lo(xv[c]), b = bf_hi(xv[c]);
          s0 += a;
          s1 += b;
          q0 = fmaf(a, a, q0);
          q1 = fmaf(b, b, q1);
          r0 = fmaf(a, wr[2 * c], r0);
          r1 = fmaf(b, wr[2 * c + 1], r1);
        }
        float s[4] = {s0 + s1, q0 + q1, r0 + r1, 0.f};
        xreduce<2, 16>(s, lane);
        xreduce<1, 8>(s, lane);
#pragma unroll
        for (int q = 5; q > 0; q--) sh[q] = sh[q - 1];
        sh[0] = s[0];
      }
      xreduce<4, 4>(sh, lane);
      xreduce<2, 2>(sh, lane);
      xreduce<1, 1>(sh, lane);
      const float mean = __shfl_sync(0xffffffffu, sh[0], lane & 7) * (1.f / D_);
      float var = fmaf(-mean, mean, __shfl_sync(0xffffffffu, sh[0], 8 + (lane & 7)) * (1.f / D_));
      const float dot = __shfl_sync(0xffffffffu, sh[0], 16 + (lane & 7));
      if (__any_sync(0xffffffffu, mean * mean > 16.f * var)) {
#pragma unroll 1
        for (int i = 0; i < nrow; i++) {
          uint32_t xv[16];
          load_row(i, xv);
          const float m = __shfl_sync(0xffffffffu, mean, nrow - 1 - i);
          float qq = 0.f;
#pragma unroll
          for (int c = 0; c < 16; c++) {
            const float a = bf_lo(xv[c]) - m, b = bf_hi(xv[c]) - m;
            qq = fmaf(a, a, fmaf(b, b, qq));
          }
          qq = warp_sum(qq) * (1.f / D_);
          if (ri == i) var = qq;
        }
      }
      const float mb = bf_round(mean);
      const float den = bf_round(sqrt_approx(bf_round(bf_round(var) + 1e-5f)));
      const float inv = rcp_approx(den);
      if (lane < nrow) st_rec(g_stat + row0 + ri, __float_as_uint(inv), __float_as_uint(mb) | tag16);
      const uint32_t u = pack_bf16(0.f, fmaf(-mb, wrsum, dot) * inv);
      const uint32_t key = lane < nrow ? ((u ^ (0x80000000u | (uint32_t)((int32_t)u >> 31))) & 0xffff0000u) | tag5 | (uint32_t)(S_ - 1 - row0 - ri) : 0u;
      const uint32_t k0 = __reduce_max_sync(0xffffffffu, key);
      const uint32_t k1 = __reduce_max_sync(0xffffffffu, key == k0 ? 0u : key);
      if (lane == 0) { st_rec(g_cand + bid * 3 + w, k0, k1); TL(26 + w); }
      const uint32_t mi = pack_bf16(mb, inv);
      uint32_t mv[6];
#pragma unroll
      for (int i = 0; i < 6; i++) mv[i] = __shfl_sync(0xffffffffu, mi, nrow - 1 - i);
#pragma unroll
      for (int i = 0; i < 6; i++) load_row(min(i, nrow - 1), xo[i]);
#pragma unroll
      for (int i = 0; i < 6; i++) fetch_row(wrow, i);
#pragma unroll
      for (int i = 0; i < 6; i++) {
        const uint32_t mb2 = __byte_perm(mv[i], 0, 0x1010), inv2 = __byte_perm(mv[i], 0, 0x3232);
#pragma unroll
        for (int c = 0; c < 16; c++) xo[i][c] = bf2_fma(bf2_sub(xo[i][c], mb2), inv2, xo[i][c]);
        if (i < 3) store_row(i);
      }
      if (t == 0) TL(16);
#pragma unroll
      for (int q = 0; q < 8; q++) sh[q] = 0.f;
#pragma unroll 1
      for (int i0 = 0; i0 < 6; i0 += 2) {
        uint32_t xv[2][16];
        cp_wait<4>();
        asm volatile("cp.async.commit_group;\ncp.async.commit_group;" ::: "memory");
        load_row(i0, xv[0]);
        load_row(min(i0 + 1, nrow - 1), xv[1]);
        float s0 = 0.f, s1 = 0.f, s2 = 0.f, s3 = 0.f;
#pragma unroll
        for (int c = 0; c < 16; c++) { s0 += bf_lo(xv[0][c]); s1 += bf_hi(xv[0][c]); s2 += bf_lo(xv[1][c]); s3 += bf_hi(xv[1][c]); }
#pragma unroll
        for (int q = 5; q > 1; q--) sh[q] = sh[q - 2];
        sh[1] = s0 + s1;
        sh[0] = s2 + s3;
      }
      xreduce<4, 4>(sh, lane);
      xreduce<2, 2>(sh, lane);
      xreduce<1, 1>(sh, lane);
      sh[0] += __shfl_xor_sync(0xffffffffu, sh[0], 8);
      sh[0] += __shfl_xor_sync(0xffffffffu, sh[0], 16);
      if (lane < 6 && 5 - lane < nrow) st_rec(g_wsum + row0 + 5 - lane, __float_as_uint(sh[0]), tag);
    }
    const int nblk = bid < NFFN ? (w ? (32 - NB0) / 2 : NB0) : 0, blk0 = w ? NB0 + (w - 1) * ((32 - NB0) / 2) : 0;
    if (t == 0) TL(2);
    const size_t guoff = (size_t)(rank * 512 + 16 * blk0 + (lane >> 3)) * F_ + (bid >> 1) * 64 + (lane & 7) * 8;
    const __nv_bfloat16 *pg = w_gate + guoff, *pu = w_up + guoff;
    auto fill = [&]() {
      pace(GU_KF);
      fetch(0, pg, IC<4 * F_>{}, nblk);
      fetch(1, pu, IC<4 * F_>{}, nblk);
      fetch(2, pg + 16 * F_, IC<4 * F_>{}, nblk);
      fetch(3, pu + 16 * F_, IC<4 * F_>{}, nblk);
      store_row(3);
      store_row(4);
      if (w == 0) store_row(5);
    };
    if (w == 0) {
      uint4 cs[4], ws[2];
      uint32_t it = 0, bad;
      auto load_ws = [&]() {
#pragma unroll
        for (int i = 0; i < 2; i++) ws[i] = ld_rec2(g_wsum + part * 1024 + eb * 128 + 2 * lane + 64 * i);
      };
      do {
#pragma unroll
        for (int i = 0; i < 4; i++) cs[i] = ld_rec2(g_stat + j * 256 + 2 * lane + 64 * i);
        bad = 0;
#pragma unroll
        for (int i = 0; i < 4; i++) bad |= ((cs[i].y ^ tag16) | (cs[i].w ^ tag16)) & 0xffffu;
      } while (poll_again(bad, it));
      load_ws();
      const uint32_t sg = (uint32_t)part << 31;
#pragma unroll
      for (int i = 0; i < 4; i++) {
        const uint32_t lo = ((cs[i].x + 0x8000u) ^ sg) >> 16;
        ((uint32_t*)(aux + OFF_COLSTAT))[32 * i + (lane & 16) + (lane & 3) * 4 + ((lane >> 2) & 3)] =
            (((uint32_t)max((int)(cs[i].z - lo + 0x8000u), 0) & 0xffff0000u) | lo) ^ sg;
        const uint32_t m0 = __byte_perm(cs[i].y, 0, 0x3232), m1 = __byte_perm(cs[i].w, 0, 0x3232);
        ((uint4*)(aux + OFF_MEAN))[64 * i + 2 * lane] = make_uint4(m0, m0, m0, m0);
        ((uint4*)(aux + OFF_MEAN))[64 * i + 2 * lane + 1] = make_uint4(m1, m1, m1, m1);
      }
      if (lane == 0) misc[0] = tag;
      while (poll_again((ws[0].y ^ tag) | (ws[0].w ^ tag) | (ws[1].y ^ tag) | (ws[1].w ^ tag), it)) load_ws();
#pragma unroll
      for (int i = 0; i < 2; i++) {
        uint32_t f[4];
#pragma unroll
        for (int h = 0; h < 2; h++) {
          const float wv = -__uint_as_float(h ? ws[i].z : ws[i].x), hi = bf_round(wv), mid = bf_round(wv - hi);
          f[2 * h] = pack_bf16(hi, mid);
          f[2 * h + 1] = pack_bf16(wv - hi - mid, 0.f);
        }
        ((uint4*)(aux + OFF_WSUM))[lane + 32 * i] = make_uint4(f[0], f[1], f[2], f[3]);
      }
      fence_proxy_async_smem();
      __syncwarp();
      if (lane == 0) { mbar_arrive(bar_stat); TL(3); }
      fill();
    } else {
      uint4 kv[6];
      uint32_t it = 0, bad;
      do {
        bad = 0;
#pragma unroll
        for (int i = 0; i < 6; i++) kv[i] = ld_rec2(g_cand + 2 * lane + 64 * i);
#pragma unroll
        for (int i = 0; i < 6; i++) bad |= (kv[i].x ^ tag5) | (kv[i].z ^ tag5);
      } while (poll_again(bad & 0xf800u, it));
      uint32_t k0 = 0, k1 = 0;
#pragma unroll
      for (int i = 0; i < 6; i++) {
        const uint32_t c0 = max(kv[i].x, kv[i].z), c1 = max(min(kv[i].x, kv[i].z), max(kv[i].y, kv[i].w));
        k1 = max(max(k1, c1), min(k0, c0));
        k0 = max(k0, c0);
      }
      const uint32_t m0 = __reduce_max_sync(0xffffffffu, k0);
      const uint32_t m1 = __reduce_max_sync(0xffffffffu, k0 == m0 ? k1 : k0);
      if (t == 32) { misc[2] = m0; misc[3] = m1; }
      {
        const int r0 = S_ - 1 - (m0 & (S_ - 1)), r1 = S_ - 1 - (m1 & (S_ - 1));
        const uint32_t* pa = (const uint32_t*)(x + (size_t)r0 * D_ + rank * 512 + (w - 1) * 256) + lane;
        const uint32_t* pb = (const uint32_t*)(x + (size_t)r1 * D_ + rank * 512 + (w - 1) * 256) + lane;
        uint32_t xa[4], xb[4];
#pragma unroll
        for (int k = 0; k < 4; k++) { xa[k] = ld_relaxed(pa + 32 * k); xb[k] = ld_relaxed(pb + 32 * k); }
        uint2 sa = ld_rec(g_stat + r0), sb = ld_rec(g_stat + r1);
        fill();
        while (poll_again(((sa.y ^ tag16) | (sb.y ^ tag16)) & 0xffffu, it)) {
          sa = ld_rec(g_stat + r0);
          sb = ld_rec(g_stat + r1);
        }
        const uint32_t ma = __byte_perm(sa.y, 0, 0x3232), mb = __byte_perm(sb.y, 0, 0x3232);
        const float ia = __uint_as_float(sa.x), ib = __uint_as_float(sb.x);
#pragma unroll
        for (int k = 0; k < 4; k++) {
          const uint32_t da = bf2_sub(xa[k], ma), db = bf2_sub(xb[k], mb);
          const uint32_t na = pack_bf16(bf_lo(da) * ia, bf_hi(da) * ia), nb = pack_bf16(bf_lo(db) * ib, bf_hi(db) * ib);
          ((float4*)xs)[(w - 1) * 128 + 32 * k + lane] = make_float4(bf_lo(na), bf_lo(nb), bf_hi(na), bf_hi(nb));
        }
      }
    }
    named_bar(1, 96);
    if (t == 0) TL(4);
    if (t == 32) {
      mbar_wait(bar_ab + 8, 0);
      mbar_wait(bar_ab + 24, 0);
      fence_proxy_async_smem();
      tma_store(&maps.ab_ld, base + A_BYTES, j * 256 + 64, part * 1024 + eb * 128);
      bulk_commit();
      mbar_arrive_cluster(bar_pub + 8, rank ^ 1);
      bulk_wait<0>();
      mbar_arrive(bar_pub);
    }
    if (t == 0) {
      auto flag = [&](int lv) {
        fence_gpu();
        st_relaxed(g_abflag + (eb * 2 + part) * 96 + lv * 32 + j, tag);
      };
      mbar_wait(bar_pub + 24, 0);
      flag(0);
      TL(9);
      mbar_wait(bar_pub, 0);
      flag(1);
      asm volatile("red.relaxed.gpu.global.add.u32 [%0], 1;" ::"l"(&g_ctr) : "memory");
      TL(19);
      mbar_wait(bar_pub + 8, 0);
      flag(2);
      TL(22);
    }
    __syncwarp();
    const int cb = bid & 15, kg = bid >> 4;
    const int ndn = w ? 9 : 10;
    const __nv_bfloat16* pd = w_down + (size_t)(kg * 448 + 16 * w + (lane >> 3)) * D_ + cb * 64 + (lane & 7) * 8;
    uint32_t sa = ring;
    uint4 v0[4], v1[4];
    float2 xv[4] = {};
    auto take = [&](uint4 (&v)[4]) {
      cp_wait<3>();
#pragma unroll
      for (int i = 0; i < 4; i++) v[i] = lds128(sa + i * 512);
    };
    auto next_down = [&](bool on) {
      fetch_to(sa, pd, IC<4 * D_>{}, on);
      pd += 48 * D_;
    };
    auto half = [&](float (&acc)[16], const uint4 (&v)[4], int h) {
      gemv8(acc, v[2 * h], xv[2 * h]);
      gemv8(acc, v[2 * h + 1], xv[2 * h + 1]);
    };
    if (nblk) {
      float ag[16], au[16];
#pragma unroll
      for (int i = 0; i < 16; i++) { ag[i] = 0.f; au[i] = 0.f; }
      const float2* xp = xs + 16 * blk0 + (lane >> 3);
      int kq = 2 * GU_K1;
      auto refill = [&](int kc, const __nv_bfloat16* p, bool gu) {
        if (kc < (kq >> 1)) pace(kq >> 1);
        kq += kq < 2 * GU_K0 ? 2 : 1;
        if (gu) fetch_to(sa, p, IC<4 * F_>{}, true);
        else next_down(true);
        sa = ring + ((sa - ring + 2048) & 8191);
      };
      take(v0);
      xv[0] = xp[0];
      xv[1] = xp[4];
      pg += 32 * F_;
      pu += 32 * F_;
      refill(0, pg, true);
#pragma unroll 1
      for (int b = 0; b < nblk; b++) {
        take(v1);
        int kc = lds32(kcur);
        xv[2] = xp[8];
        xv[3] = xp[12];
        xp += 16;
        pg += 16 * F_;
        half(ag, v0, 0);
        refill(kc, pu, b + 2 < nblk);
        half(ag, v0, 1);
        take(v0);
        kc = lds32(kcur);
        pu += 16 * F_;
        half(au, v1, 0);
        xv[0] = xp[0];
        xv[1] = xp[4];
        refill(kc, pg, b + 3 < nblk);
        half(au, v1, 1);
      }
      float s[32];
#pragma unroll
      for (int i = 0; i < 16; i++) { s[i] = ag[i]; s[16 + i] = au[i]; }
      xreduce<16, 16>(s, lane);
      xreduce<8, 8>(s, lane);
      mbar_wait(bar_pub + 8, 0);
      const uint32_t dst = mapa(auxs + OFF_GU + (rank * 3 + w) * 512 + (lane >> 4) * 256 + (lane & 3) * 64 + (lane & 8) * 4, (lane >> 2) & 1);
      const uint32_t dbar = mapa(bar_gu, (lane >> 2) & 1);
      st_async4(dst, s[0], s[1], s[2], s[3], dbar);
      st_async4(dst + 16, s[4], s[5], s[6], s[7], dbar);
      if (w == 0) {
        if (lane == 0) mbar_expect_tx(bar_gu, 6 * 512);
        mbar_wait(bar_gu, 0);
        const float2* r2 = (const float2*)(aux + OFF_GU) + lane;
        float2 g2 = r2[0], u2 = r2[32];
#pragma unroll
        for (int q = 1; q < 6; q++) {
          const float2 a = r2[64 * q], c = r2[64 * q + 32];
          g2.x += a.x; g2.y += a.y; u2.x += c.x; u2.y += c.y;
        }
        float hv[2];
#pragma unroll
        for (int tok = 0; tok < 2; tok++) {
          const float g = bf_round(tok ? g2.y : g2.x), u = bf_round(tok ? u2.y : u2.x);
          hv[tok] = bf_round(__fdividef(g, 1.f + __expf(-g))) * u;
        }
        st_rec(g_h + bid * 32 + lane, pack_bf16(hv[0], hv[1]), tag);
        if (lane == 0) TL(5);
      }
    } else {
#pragma unroll
      for (int u = 0; u < 4; u++) fetch(u, pd + u * 48 * D_, IC<4 * D_>{}, true);
      pd += 4 * 48 * D_;
      take(v0);
      next_down(true);
      sa += 2048;
      pace(H_K);
    }
    if (t == 64) prefetch_l2(out + (size_t)bid * 16 * D_, 16 * D_ * 2);
    if (t == 32) wait_out_init(tag);
    named_bar(1, 96);
    {
      uint4 hv[3];
      uint32_t it = 0;
      bool bad[3] = {true, true, w == 0};
      while (true) {
#pragma unroll
        for (int i = 0; i < 3; i++) if (bad[i]) hv[i] = ld_rec2(g_h + kg * 448 + 2 * (t + 96 * i));
#pragma unroll
        for (int i = 0; i < 3; i++) bad[i] = bad[i] && (hv[i].y != tag || hv[i].w != tag);
        if (!poll_again(bad[0] || bad[1] || bad[2], it)) break;
        __nanosleep(100);
      }
#pragma unroll
      for (int i = 0; i < 3; i++) {
        if (t + 96 * i < 224) ((float4*)xs)[t + 96 * i] = make_float4(bf_lo(hv[i].x), bf_hi(hv[i].x), bf_lo(hv[i].z), bf_hi(hv[i].z));
      }
    }
    named_bar(1, 96);
    if (t == 0) TL(10);
    {
      float ay[16];
#pragma unroll
      for (int q = 0; q < 16; q++) ay[q] = 0.f;
      const float2* hp = xs + 16 * w + (lane >> 3);
      xv[0] = hp[0];
      xv[1] = hp[4];
      auto unit = [&](const uint4 (&v)[4], uint4 (&vn)[4], int u) {
        take(vn);
        xv[2] = hp[8];
        xv[3] = hp[12];
        hp += 48;
        half(ay, v, 0);
        xv[0] = hp[0];
        xv[1] = hp[4];
        next_down(u + 5 < ndn);
        sa = ring + ((sa - ring + 2048) & 8191);
        half(ay, v, 1);
      };
#pragma unroll 1
      for (int u = 0; u < ndn; u += 2) {
        unit(v0, v1, u);
        if (u + 1 < ndn) unit(v1, v0, u + 1);
      }
      xreduce<8, 16>(ay, lane);
      xreduce<4, 8>(ay, lane);
      ((float4*)red)[w * 32 + (lane & 7) * 4 + (lane >> 3)] = make_float4(ay[0], ay[1], ay[2], ay[3]);
    }
    named_bar(1, 96);
    if (t < 64) {
      const float* r = red + 4 * lane + w;
      const uint32_t key = misc[2 + w];
      const uint32_t rb = (key ^ (0x80000000u | ~(uint32_t)((int32_t)key >> 31))) & 0xffff0000u;
      const float gate = bf_round(__fdividef(1.f, 1.f + __expf(-__uint_as_float(rb))));
      const uint32_t v = pack_bf16((r[0] + r[128] + r[256]) * gate, (r[2] + r[130] + r[258]) * gate);
      asm volatile("red.relaxed.gpu.global.add.noftz.bf16x2 [%0], %1;"
                   ::"l"(out + (size_t)(S_ - 1 - (key & (S_ - 1))) * D_ + cb * 64 + 2 * lane), "r"(v) : "memory");
      if (t == 0) TL(6);
    }
  } else {
    float acc[128];
    const int wg = warp >> 2, wi = warp & 3;
    const bool elect = (tid & 127) == 0;
    const uint32_t a_base = base + wg * (A_BYTES / 2);

    auto release = [&](int k) {
      if (elect) mbar_arrive(empty0 + 8 * (k & 3));
    };
    auto mma_step = [&](int st, int scale_d) {
      const uint64_t da = make_desc(a_base + st * A_BYTES), db = make_desc(base + OFF_B + st * B_BYTES);
      wgmma_fence();
      wgmma_n256(acc, da, db, scale_d);
      wgmma_n256(acc, da + 2, db + 2, 1);
      wgmma_n256(acc, da + 4, db + 4, 1);
      wgmma_commit();
      wgmma_n256(acc, da + 6, db + 6, 1);
      wgmma_commit();
    };
    auto stamp = [&](int k) {
      if (elect) TK(wg, k);
    };

#pragma unroll 1
    for (int k = 0; k < K1; k++) {
      if (k == 0) {
        cp_wait<0>();
        fence_proxy_async_smem();
        named_bar(4, 256);
        if (tid == 0) mbar_arrive(full0);
        stamp(k);
      } else {
        stamp(k);
        mbar_wait(full0 + 8 * (k & 3), (k >> 2) & 1);
        TKC(k);
      }
      mma_step(k & 3, k);
      wgmma_wait<2>();
      if (k) release(k - 1);
    }
    {
      mbar_wait(bar_stat, 0);
      uint32_t af[2];
#pragma unroll
      for (int h = 0; h < 2; h++) {
        af[h] = lds32(auxs + OFF_WSUM + (wg * 64 + wi * 16 + h * 8 + (lane >> 2)) * 8 + (lane & 1) * 4);
        if (lane & 2) af[h] = 0;
      }
      wgmma_fence();
      wgmma_n256_rs(acc, af[0], af[1], 0u, 0u, (uint64_t)(((auxs + OFF_MEAN) & 0x3FFFF) >> 4) | ((uint64_t)8 << 32));
      wgmma_commit();
      const uint32_t dst = __shfl_sync(0xffffffffu, a_base + (wi * 16 + (lane & 15)) * 128 + (((lane >> 4) ^ (lane & 7)) << 4), lane);
      const uint32_t cst = auxs + OFF_COLSTAT + (lane & 3) * 16;
      uint4 cn[8];
#pragma unroll
      for (int p = 0; p < 4; p++) cn[p] = lds128(cst + p * 64);
      mbar_wait(full0, 0);
      wgmma_wait<1>();
      release(K1 - 1);
      wgmma_wait<0>();
      if (elect) TL(12 + wg);
#pragma unroll
      for (int p = 0; p < 16; p++) {
        const uint32_t c0 = p & 1 ? cn[p >> 1].z : cn[p >> 1].x, c1 = p & 1 ? cn[p >> 1].w : cn[p >> 1].y;
        const float4 c = make_float4(bf_lo(c0), __uint_as_float(c0), bf_lo(c1), __uint_as_float(c1));
        stmatrix_x4((dst ^ ((p & 3) << 5)) + (p >> 2) * A_BYTES, pack_bf16(acc[8 * p] * c.x, acc[8 * p + 1] * c.y),
                    pack_bf16(acc[8 * p + 2] * c.x, acc[8 * p + 3] * c.y), pack_bf16(acc[8 * p + 4] * c.z, acc[8 * p + 5] * c.w),
                    pack_bf16(acc[8 * p + 6] * c.z, acc[8 * p + 7] * c.w));
        if (p == 3 || p == 15) {
          if (p == 3) fence_proxy_async_smem();
          __syncwarp();
          if (lane == 0) mbar_arrive(bar_ab + 16 * wg + (p & 8));
        }
        if (p == 3) {
#pragma unroll
          for (int q = 4; q < 8; q++) cn[q] = lds128(cst + q * 64);
        }
      }
      named_bar(2 + wg, 128);
      if (elect) TL(29 + wg);
    }
#pragma unroll
    for (int i = 0; i < 128; i++) asm volatile("" : "=f"(acc[i]));
    stamp(K1);
    mma_step(0, 0);
    mbar_wait(bar_ab + 16 * wg + 8, 0);
    fence_proxy_async_smem();
#pragma unroll 1
    for (int k = K1 + 1; k < KT - 4; k++) {
      const bool early = k == K1 + 4;
      if (early) {
        wgmma_wait<0>();
        release(k - 1);
      }
      stamp(k);
      mbar_wait(full0 + 8 * (k & 3), (k >> 2) & 1);
      TKC(k);
      mma_step(k & 3, 1);
      wgmma_wait<2>();
      if (!early) release(k - 1);
    }
    const bool second = wg == 0;
    auto turn = [&](auto oc, uint32_t a, int hs) {
      const uint64_t da = make_desc(a), db = make_desc(base + OFF_B + hs * (B_BYTES / 2));
      wgmma_fence();
#pragma unroll
      for (int q = 0; q < 4; q++) wgmma_n128<decltype(oc)::value>(acc, da + 2 * q, db + 2 * q);
      wgmma_commit();
    };
    const uint32_t a3 = base + OFF_B + 3 * (B_BYTES / 2) + wg * (A_BYTES / 2);
    const uint32_t o0 = ((lane >> 4) * 8 + (lane & 7)) * 128 + (((2 * wi + ((lane >> 3) & 1)) ^ (lane & 7)) << 4);
    auto send = [&](auto oc, uint32_t dst, uint32_t pitch) {
      constexpr int O = decltype(oc)::value;
#pragma unroll
      for (int h = 0; h < 2; h++) {
#pragma unroll
        for (int p = 0; p < 4; p++) {
          const float* v = acc + O + 32 * h + 8 * p;
          stmatrix_x4_t(dst + h * pitch + o0 + p * 2048, pack_bf16(v[0], v[1]), pack_bf16(v[2], v[3]), pack_bf16(v[4], v[5]), pack_bf16(v[6], v[7]));
        }
        fence_proxy_async_smem();
        named_bar(2 + wg, 128);
        if (elect) {
          tma_red_add(&maps.out, dst + h * pitch, eb * 128 + wg * 64, (j * 4 + O / 32 + h) * (PR / 4));
          if (h == 0) TL(24 + (O / 32) + second + 9);
        }
        __syncwarp();
      }
    };
    const float one = __uint_as_float(__shfl_sync(0xffffffffu, lds32(kcur) >> 8, 0) | 0x3f800000u);
    auto cut = [&](int lo) {
#pragma unroll
      for (int i = lo; i < lo + 64; i++) acc[i] *= one;
    };
    mbar_wait(full0, 1);
    wgmma_wait<0>();
    release(KT - 5);
    cut(0);
    if (second) {
      mbar_wait(full0 + 8, 1);
      mbar_wait(full0 + 16, 1);
      named_bar(4, 256);
    }
    stamp(KT - 4);
    turn(IC<0>{}, a_base, 0);
    if (!second) mbar_wait(full0 + 8, 1);
    turn(IC<0>{}, a_base + A_BYTES, 2);
    if (!second) mbar_wait(full0 + 16, 1);
    turn(IC<0>{}, a_base + 2 * A_BYTES, 4);
    wgmma_wait<2>();
    release(0);
    turn(IC<0>{}, a3, 5);
    named_arrive(4 + second, 256);
    stamp(KT - 3);
    if (elect) {
      mbar_wait(bar_out + 8, 0);
      fence_proxy_async();
    }
    __syncwarp();
    mbar_wait(second ? bar_out : empty0 + 24, 0);
    wgmma_wait<2>();
    if (second) named_bar(2 + wg, 128);
    wgmma_wait<0>();
    if (elect && !second) mbar_arrive(bar_out);
    if (elect) TL(24 + second);
    send(IC<0>{}, second ? base + OFF_B + B_BYTES : base + 3 * A_BYTES, A_BYTES / 2);
    cut(64);
    mbar_wait(full0 + 24, 1);
    if (second) mbar_wait(full0, 0);
    named_bar(5 + second, 256);
    stamp(KT - 2);
    turn(IC<64>{}, a_base, 1);
    turn(IC<64>{}, a_base + A_BYTES, 6);
    turn(IC<64>{}, a_base + 2 * A_BYTES, 7);
    if (!second) mbar_wait(full0, 0);
    turn(IC<64>{}, a3, 0);
    if (!second) named_arrive(6, 256);
    stamp(KT - 1);
    wgmma_wait<2>();
    named_bar(2 + wg, 128);
    wgmma_wait<0>();
    if (elect) TL(20 + second);
    send(IC<64>{}, a_base, A_BYTES);
    if (elect) {
      bulk_commit();
      bulk_wait_read<0>();
      if (second) TL(18);
    }
  }
}

typedef CUresult (*EncodeFn)(CUtensorMap*, CUtensorMapDataType, cuuint32_t, void*, const cuuint64_t*, const cuuint64_t*, const cuuint32_t*,
                             const cuuint32_t*, CUtensorMapInterleave, CUtensorMapSwizzle, CUtensorMapL2promotion, CUtensorMapFloatOOBfill);

void make_map(EncodeFn enc, CUtensorMap* m, void* ptr, uint64_t rows, uint64_t cols, uint32_t box_rows, CUtensorMapL2promotion promo,
              uint32_t box_cols = 64, CUtensorMapSwizzle sw = CU_TENSOR_MAP_SWIZZLE_128B) {
  cuuint64_t dims[2] = {cols, rows};
  cuuint64_t strides[1] = {cols * 2};
  cuuint32_t box[2] = {box_cols, box_rows};
  cuuint32_t es[2] = {1, 1};
  enc(m, CU_TENSOR_MAP_DATA_TYPE_BFLOAT16, 2, ptr, dims, strides, box, es, CU_TENSOR_MAP_INTERLEAVE_NONE, sw, promo,
      CU_TENSOR_MAP_FLOAT_OOB_FILL_NONE);
}

void make_map5(EncodeFn enc, CUtensorMap* m, void* ptr, uint64_t cols, uint32_t box_rows, uint32_t box_cols, CUtensorMapSwizzle sw) {
  cuuint64_t dims[5] = {cols, 2, 2, PG, 512 / PG};
  cuuint64_t strides[4] = {cols * 2 * 1024, cols * 2 * 512, cols * 2 * (512 / PG), cols * 2};
  cuuint32_t box[5] = {box_cols, 2, 2, PG, box_rows / (4 * PG)};
  cuuint32_t es[5] = {1, 1, 1, 1, 1};
  enc(m, CU_TENSOR_MAP_DATA_TYPE_BFLOAT16, 5, ptr, dims, strides, box, es, CU_TENSOR_MAP_INTERLEAVE_NONE, sw,
      CU_TENSOR_MAP_L2_PROMOTION_L2_128B, CU_TENSOR_MAP_FLOAT_OOB_FILL_NONE);
}

}

extern "C" void kernel_launch(void* const* d_in, const int* in_sizes, int n_in, void* d_out, int out_size) {
  (void)in_sizes; (void)n_in; (void)out_size;
  void* fn = nullptr;
  cudaDriverEntryPointQueryResult qr;
  cudaGetDriverEntryPoint("cuTensorMapEncodeTiled", &fn, cudaEnableDefault, &qr);
  EncodeFn enc = (EncodeFn)fn;
  void* ab = nullptr;
  cudaGetSymbolAddress(&ab, g_ab);
  Maps maps;
  const CUtensorMapL2promotion P256 = CU_TENSOR_MAP_L2_PROMOTION_L2_256B, P128 = CU_TENSOR_MAP_L2_PROMOTION_L2_128B;
  make_map(enc, &maps.x, d_in[0], S_, D_, 256, P256);
  for (int p = 0; p < 2; p++) {
    make_map5(enc, &maps.ws[p], d_in[1 + p], S_, 256, 64, CU_TENSOR_MAP_SWIZZLE_128B);
    make_map5(enc, &maps.ws_h[p], d_in[1 + p], S_, 128, 64, CU_TENSOR_MAP_SWIZZLE_128B);
    make_map5(enc, &maps.ws_pf[p], d_in[1 + p], S_, 32, 128, CU_TENSOR_MAP_SWIZZLE_NONE);
  }
  make_map(enc, &maps.wd[0], d_in[3], D_, D_, 128, P256);
  make_map(enc, &maps.wd[1], d_in[4], D_, D_, 128, P256);
  make_map(enc, &maps.ab_ld, ab, 2 * D_, S_, 128, P128);
  make_map(enc, &maps.ab_st, ab, 2 * D_, S_, 64, P128);
  make_map5(enc, &maps.out, d_out, D_, 64, 64, CU_TENSOR_MAP_SWIZZLE_128B);
  cudaFuncSetAttribute(fused_kernel, cudaFuncAttributeMaxDynamicSharedMemorySize, SMEM_BYTES);
  fused_kernel<<<NCTA, 384, SMEM_BYTES, cudaStreamPerThread>>>(
      (const __nv_bfloat16*)d_in[0], (const __nv_bfloat16*)d_in[3], (const __nv_bfloat16*)d_in[4], (const __nv_bfloat16*)d_in[6],
      (const __nv_bfloat16*)d_in[7], (const __nv_bfloat16*)d_in[8], maps, (const __nv_bfloat16*)d_in[9], (__nv_bfloat16*)d_out);
}
```

```cpp
#include <cuda_runtime.h>
#include <cuda_bf16.h>
#include <cuda.h>
#include <stdint.h>

#define DEVI __device__ __forceinline__

namespace {

constexpr int S_ = 2048, D_ = 1024, F_ = 3584;
constexpr int STAGES = 4;
constexpr int A_BYTES = 128 * 64 * 2, B_BYTES = 256 * 64 * 2;
constexpr int K1 = 16, K2 = 32, KT = K1 + K2;
constexpr int NCTA = 128;
constexpr int NFFN = 112;
constexpr int PG = 4;
constexpr int PR = 64 / PG;
constexpr int NMIR = 4;
constexpr int NB0 = 8;
constexpr int LN_K0 = 4;
constexpr int GU_KF = 15;
constexpr int GU_K1 = 22;
constexpr int GU_K0 = 24;
constexpr int H_K = 30;
constexpr unsigned long long WS_MASK = 0x1a0000fff80ull;

constexpr int OFF_B = STAGES * A_BYTES;
constexpr int OFF_AUX = OFF_B + STAGES * B_BYTES;
constexpr int OFF_RING = 0;
constexpr int OFF_XS = OFF_RING + 3 * 8192;
constexpr int OFF_GU = OFF_XS + 4096;
constexpr int OFF_MEAN = OFF_GU;
constexpr int OFF_COLSTAT = OFF_XS + 8192;
constexpr int OFF_RED = OFF_COLSTAT;
constexpr int OFF_WSUM = OFF_COLSTAT + 512;
constexpr int OFF_FLAGS = OFF_COLSTAT + 1536;
constexpr int OFF_BAR = OFF_COLSTAT + 2048;
constexpr int OFF_MISC = OFF_BAR + 224;
constexpr int AUX_BYTES = OFF_MISC + 32;
constexpr int SMEM_BYTES = OFF_AUX + AUX_BYTES;
static_assert(SMEM_BYTES <= 232448, "smem");

template <int V> struct IC { static constexpr int value = V; };

struct Maps {
  CUtensorMap x, wd[2], ws[2], ws_h[2], ws_pf[2], ab_ld, ab_st, out;
};

__device__ __nv_bfloat16 g_ab[2 * D_ * S_];
__device__ uint2 g_stat[S_];
__device__ uint2 g_wsum[2 * D_];
__device__ uint2 g_cand[NCTA * 3];
__device__ uint2 g_h[F_];
__device__ __align__(128) uint32_t g_abflag[16 * 3 * 32];
__device__ uint32_t g_ctr;
#define TL(i) do {} while (0)
#define TK(r, k) do {} while (0)

#define TKP(r, k) TK(r, k)
#define TKC(k)
DEVI uint32_t smem_u32(const void* p) { return (uint32_t)__cvta_generic_to_shared(p); }
DEVI void mbar_init(uint32_t bar, uint32_t cnt) { asm volatile("mbarrier.init.shared::cta.b64 [%0], %1;" ::"r"(bar), "r"(cnt) : "memory"); }
DEVI void mbar_expect_tx(uint32_t bar, uint32_t bytes) { asm volatile("mbarrier.arrive.expect_tx.shared::cta.b64 _, [%0], %1;" ::"r"(bar), "r"(bytes) : "memory"); }
DEVI void mbar_arrive(uint32_t bar) { asm volatile("mbarrier.arrive.shared::cta.b64 _, [%0];" ::"r"(bar) : "memory"); }
DEVI void mbar_arrive_cluster(uint32_t bar, uint32_t cta) {
  asm volatile("{\n.reg .b32 ra;\nmapa.shared::cluster.u32 ra, %0, %1;\nmbarrier.arrive.shared::cluster.b64 _, [ra];\n}" ::"r"(bar), "r"(cta) : "memory");
}
DEVI uint32_t mapa(uint32_t a, uint32_t cta) { uint32_t r; asm("mapa.shared::cluster.u32 %0, %1, %2;" : "=r"(r) : "r"(a), "r"(cta)); return r; }
DEVI void st_async4(uint32_t dst, float a, float b, float c, float d, uint32_t bar) {
  asm volatile("st.async.shared::cluster.mbarrier::complete_tx::bytes.v4.f32 [%0], {%1, %2, %3, %4}, [%5];"
               ::"r"(dst), "f"(a), "f"(b), "f"(c), "f"(d), "r"(bar) : "memory");
}
DEVI bool mbar_try_wait(uint32_t bar, uint32_t parity) {
  uint32_t ok;
  asm volatile("{\n.reg .pred p;\nmbarrier.try_wait.parity.shared::cta.b64 p, [%1], %2;\nselp.u32 %0, 1, 0, p;\n}" : "=r"(ok) : "r"(bar), "r"(parity) : "memory");
  return ok;
}
DEVI bool mbar_test(uint32_t bar, uint32_t parity) {
  uint32_t ok;
  asm volatile("{\n.reg .pred p;\nmbarrier.test_wait.parity.shared::cta.b64 p, [%1], %2;\nselp.u32 %0, 1, 0, p;\n}" : "=r"(ok) : "r"(bar), "r"(parity) : "memory");
  return ok;
}
DEVI void mbar_wait(uint32_t bar, uint32_t parity) {
  uint32_t n = 0;
  while (!mbar_try_wait(bar, parity)) { if (++n > (1u << 20)) __trap(); }
}
DEVI void tma_load(uint32_t dst, const CUtensorMap* m, int c0, int c1, uint32_t bar) {
  asm volatile("cp.async.bulk.tensor.2d.shared::cluster.global.mbarrier::complete_tx::bytes [%0], [%1, {%3, %4}], [%2];"
               ::"r"(dst), "l"(m), "r"(bar), "r"(c0), "r"(c1) : "memory");
}
DEVI void tma_load5(uint32_t dst, const CUtensorMap* m, int c0, int c4, uint32_t bar) {
  asm volatile("cp.async.bulk.tensor.5d.shared::cluster.global.mbarrier::complete_tx::bytes [%0], [%1, {%3, %5, %5, %5, %4}], [%2];"
               ::"r"(dst), "l"(m), "r"(bar), "r"(c0), "r"(c4), "r"(0) : "memory");
}
DEVI void tma_store(const CUtensorMap* m, uint32_t src, int c0, int c1) {
  asm volatile("cp.async.bulk.tensor.2d.global.shared::cta.bulk_group [%0, {%2, %3}], [%1];" ::"l"(m), "r"(src), "r"(c0), "r"(c1) : "memory");
}
DEVI void tma_red_add(const CUtensorMap* m, uint32_t src, int c0, int c1) {
  asm volatile("cp.reduce.async.bulk.tensor.5d.global.shared::cta.add.bulk_group [%0, {%2, %4, %4, %4, %3}], [%1];" ::"l"(m), "r"(src), "r"(c0), "r"(c1), "r"(0) : "memory");
}
DEVI uint4 lds128(uint32_t a) { uint4 v; asm volatile("ld.shared.v4.u32 {%0,%1,%2,%3}, [%4];" : "=r"(v.x), "=r"(v.y), "=r"(v.z), "=r"(v.w) : "r"(a) : "memory"); return v; }
DEVI uint32_t lds32(uint32_t a) { uint32_t v; asm volatile("ld.volatile.shared.u32 %0, [%1];" : "=r"(v) : "r"(a) : "memory"); return v; }
DEVI void sts32(uint32_t a, uint32_t v) { asm volatile("st.volatile.shared.u32 [%0], %1;" ::"r"(a), "r"(v) : "memory"); }
DEVI void tma_prefetch(const CUtensorMap* m, int c0, int c1) {
  asm volatile("cp.async.bulk.prefetch.tensor.5d.L2.global [%0, {%1, %3, %3, %3, %2}];" ::"l"(m), "r"(c0), "r"(c1), "r"(0) : "memory");
}
DEVI void cp_async16(uint32_t dst, const void* src) { asm volatile("cp.async.cg.shared.global [%0], [%1], 16;" ::"r"(dst), "l"(src) : "memory"); }
DEVI void cp_async16_once(uint32_t dst, const void* src) {
  asm volatile("{\n.reg .b64 pol;\ncreatepolicy.fractional.L2::evict_first.b64 pol, 1.0;\n"
               "cp.async.cg.shared.global.L2::cache_hint [%0], [%1], 16, pol;\n}" ::"r"(dst), "l"(src) : "memory");
}
DEVI bool elect_one() {
  uint32_t p;
  asm volatile("{\n.reg .pred P;\nelect.sync _|P, 0xffffffff;\nselp.u32 %0, 1, 0, P;\n}" : "=r"(p));
  return p;
}
DEVI float sqrt_approx(float v) { float r; asm("sqrt.approx.ftz.f32 %0, %1;" : "=f"(r) : "f"(v)); return r; }
DEVI float rcp_approx(float v) { float r; asm("rcp.approx.ftz.f32 %0, %1;" : "=f"(r) : "f"(v)); return r; }
DEVI void bulk_commit() { asm volatile("cp.async.bulk.commit_group;" ::: "memory"); }
template <int N> DEVI void bulk_wait() { asm volatile("cp.async.bulk.wait_group %0;" ::"n"(N) : "memory"); }
template <int N> DEVI void bulk_wait_read() { asm volatile("cp.async.bulk.wait_group.read %0;" ::"n"(N) : "memory"); }
DEVI void fence_proxy_async() { asm volatile("fence.proxy.async.global;" ::: "memory"); }
DEVI void fence_proxy_async_smem() { asm volatile("fence.proxy.async.shared::cta;" ::: "memory"); }
DEVI void prefetch_map(const CUtensorMap* m) { asm volatile("prefetch.tensormap [%0];" ::"l"(m) : "memory"); }
DEVI void named_bar(int id, int n) { asm volatile("bar.sync %0, %1;" ::"r"(id), "r"(n) : "memory"); }
DEVI void named_arrive(int id, int n) { asm volatile("bar.arrive %0, %1;" ::"r"(id), "r"(n) : "memory"); }
DEVI void wgmma_fence() { asm volatile("wgmma.fence.sync.aligned;" ::: "memory"); }
DEVI void wgmma_commit() { asm volatile("wgmma.commit_group.sync.aligned;" ::: "memory"); }
template <int N> DEVI void wgmma_wait() { asm volatile("wgmma.wait_group.sync.aligned %0;" ::"n"(N) : "memory"); }
DEVI uint64_t make_desc(uint32_t addr) {
  return (uint64_t)((addr & 0x3FFFF) >> 4) | ((uint64_t)1 << 16) | ((uint64_t)64 << 32) | ((uint64_t)1 << 62);
}
DEVI uint32_t ld_acquire(const uint32_t* p) { uint32_t v; asm volatile("ld.acquire.gpu.global.u32 %0, [%1];" : "=r"(v) : "l"(p) : "memory"); return v; }
DEVI void fence_gpu() { asm volatile("fence.acq_rel.gpu;" ::: "memory"); }
DEVI uint32_t ld_relaxed(const uint32_t* p) { uint32_t v; asm volatile("ld.relaxed.gpu.global.u32 %0, [%1];" : "=r"(v) : "l"(p) : "memory"); return v; }
DEVI void st_rec(uint2* p, uint32_t a, uint32_t b) {
  asm volatile("{\n.reg .b64 t;\nmov.b64 t, {%1, %2};\nst.relaxed.gpu.global.b64 [%0], t;\n}" ::"l"(p), "r"(a), "r"(b) : "memory");
}
DEVI uint4 ld_rec2(const uint2* p) {
  uint4 v;
  asm volatile("{\n.reg .b64 a, b;\nld.relaxed.gpu.global.v2.b64 {a, b}, [%4];\nmov.b64 {%0, %1}, a;\nmov.b64 {%2, %3}, b;\n}"
               : "=r"(v.x), "=r"(v.y), "=r"(v.z), "=r"(v.w) : "l"(p) : "memory");
  return v;
}
DEVI uint2 ld_rec(const uint2* p) {
  uint2 v;
  asm volatile("{\n.reg .b64 a;\nld.relaxed.gpu.global.b64 a, [%2];\nmov.b64 {%0, %1}, a;\n}" : "=r"(v.x), "=r"(v.y) : "l"(p) : "memory");
  return v;
}
DEVI bool poll_again(bool bad, uint32_t& it) {
  if (!__any_sync(0xffffffffu, bad)) return false;
  if (++it > (1u << 18)) __trap();
  __nanosleep(40);
  return true;
}
DEVI void st_relaxed(uint32_t* p, uint32_t v) { asm volatile("st.relaxed.gpu.global.u32 [%0], %1;" ::"l"(p), "r"(v) : "memory"); }
DEVI uint32_t pack_bf16(float lo, float hi) { uint32_t r; asm("cvt.rn.bf16x2.f32 %0, %1, %2;" : "=r"(r) : "f"(hi), "f"(lo)); return r; }
DEVI float bf_lo(uint32_t v) { return __uint_as_float(v << 16); }
DEVI float bf_hi(uint32_t v) { return __uint_as_float(v & 0xffff0000u); }
DEVI float bf_round(float v) { return bf_hi(pack_bf16(0.f, v)); }
DEVI uint32_t bf2_sub(uint32_t a, uint32_t b) { uint32_t r; asm("sub.rn.bf16x2 %0, %1, %2;" : "=r"(r) : "r"(a), "r"(b)); return r; }
DEVI uint32_t bf2_fma(uint32_t a, uint32_t b, uint32_t c) { uint32_t r; asm("fma.rn.bf16x2 %0, %1, %2, %3;" : "=r"(r) : "r"(a), "r"(b), "r"(c)); return r; }
DEVI void prefetch_l2(const void* p, uint32_t bytes) { asm volatile("cp.async.bulk.prefetch.L2.global [%0], %1;" ::"l"(p), "r"(bytes) : "memory"); }
DEVI void stmatrix_x4(uint32_t addr, uint32_t a, uint32_t b, uint32_t c, uint32_t d) {
  asm volatile("stmatrix.sync.aligned.m8n8.x4.shared.b16 [%0], {%1,%2,%3,%4};" ::"r"(addr), "r"(a), "r"(b), "r"(c), "r"(d) : "memory");
}
DEVI void stmatrix_x4_t(uint32_t addr, uint32_t a, uint32_t b, uint32_t c, uint32_t d) {
  asm volatile("stmatrix.sync.aligned.m8n8.x4.trans.shared.b16 [%0], {%1,%2,%3,%4};" ::"r"(addr), "r"(a), "r"(b), "r"(c), "r"(d) : "memory");
}
DEVI void gemv8(float (&acc)[16], const uint4& v, const float2 xv) {
  const uint32_t g4[4] = {v.x, v.y, v.z, v.w};
#pragma unroll
  for (int c = 0; c < 4; c++) {
    const float lo = bf_lo(g4[c]), hi = bf_hi(g4[c]);
    acc[4 * c + 0] = fmaf(lo, xv.x, acc[4 * c + 0]);
    acc[4 * c + 1] = fmaf(lo, xv.y, acc[4 * c + 1]);
    acc[4 * c + 2] = fmaf(hi, xv.x, acc[4 * c + 2]);
    acc[4 * c + 3] = fmaf(hi, xv.y, acc[4 * c + 3]);
  }
}
template <int H, int MASK, int N> DEVI void xreduce(float (&s)[N], int lane) {
  const bool up = lane & MASK;
#pragma unroll
  for (int i = 0; i < H; i++) {
    const float keep = up ? s[i + H] : s[i], send = up ? s[i] : s[i + H];
    s[i] = keep + __shfl_xor_sync(0xffffffffu, send, MASK);
  }
}
DEVI float warp_sum(float v) {
#pragma unroll
  for (int o = 16; o; o >>= 1) v += __shfl_xor_sync(0xffffffffu, v, o);
  return v;
}

#define ACC128 \
      "{%0,%1,%2,%3,%4,%5,%6,%7,%8,%9,%10,%11,%12,%13,%14,%15,%16,%17,%18,%19,%20,%21,%22,%23,%24,%25,%26,%27,%28,%29,%30,%31," \
      "%32,%33,%34,%35,%36,%37,%38,%39,%40,%41,%42,%43,%44,%45,%46,%47,%48,%49,%50,%51,%52,%53,%54,%55,%56,%57,%58,%59,%60,%61,%62,%63," \
      "%64,%65,%66,%67,%68,%69,%70,%71,%72,%73,%74,%75,%76,%77,%78,%79,%80,%81,%82,%83,%84,%85,%86,%87,%88,%89,%90,%91,%92,%93,%94,%95," \
      "%96,%97,%98,%99,%100,%101,%102,%103,%104,%105,%106,%107,%108,%109,%110,%111,%112,%113,%114,%115,%116,%117,%118,%119,%120,%121,%122,%123,%124,%125,%126,%127},"
#define R128(d) R8(d, 0), R8(d, 8), R8(d, 16), R8(d, 24), R8(d, 32), R8(d, 40), R8(d, 48), R8(d, 56), R8(d, 64), R8(d, 72), R8(d, 80), \
                R8(d, 88), R8(d, 96), R8(d, 104), R8(d, 112), R8(d, 120)
#define R8(d, i) "+f"(d[i]), "+f"(d[i + 1]), "+f"(d[i + 2]), "+f"(d[i + 3]), "+f"(d[i + 4]), "+f"(d[i + 5]), "+f"(d[i + 6]), "+f"(d[i + 7])
DEVI void wgmma_n256(float (&d)[128], uint64_t da, uint64_t db, int scale_d) {
  asm volatile("{\n.reg .pred p;\nsetp.ne.b32 p, %130, 0;\nwgmma.mma_async.sync.aligned.m64n256k16.f32.bf16.bf16 " ACC128
               " %128, %129, p, 1, 1, 0, 0;\n}\n" : R128(d) : "l"(da), "l"(db), "r"(scale_d));
}
DEVI void wgmma_n256_rs(float (&d)[128], uint32_t a0, uint32_t a1, uint32_t a2, uint32_t a3, uint64_t db) {
  asm volatile("wgmma.mma_async.sync.aligned.m64n256k16.f32.bf16.bf16 " ACC128 " {%128, %129, %130, %131}, %132, 1, 1, 1, 0;\n"
               : R128(d) : "r"(a0), "r"(a1), "r"(a2), "r"(a3), "l"(db));
}

#define ACC64 \
      "{%0,%1,%2,%3,%4,%5,%6,%7,%8,%9,%10,%11,%12,%13,%14,%15,%16,%17,%18,%19,%20,%21,%22,%23,%24,%25,%26,%27,%28,%29,%30,%31," \
      "%32,%33,%34,%35,%36,%37,%38,%39,%40,%41,%42,%43,%44,%45,%46,%47,%48,%49,%50,%51,%52,%53,%54,%55,%56,%57,%58,%59,%60,%61,%62,%63},"
template <int O> DEVI void wgmma_n128(float (&d)[128], uint64_t da, uint64_t db) {
  asm volatile("wgmma.mma_async.sync.aligned.m64n128k16.f32.bf16.bf16 " ACC64 " %64, %65, 1, 1, 1, 0, 0;\n"
               : R8(d, O), R8(d, O + 8), R8(d, O + 16), R8(d, O + 24), R8(d, O + 32), R8(d, O + 40), R8(d, O + 48), R8(d, O + 56)
               : "l"(da), "l"(db));
}

DEVI void wait_out_init(uint32_t tag) {
  uint32_t it = 0;
  while ((int32_t)(ld_acquire(&g_ctr) - tag) < 0) { if (++it > (1u << 20)) __trap(); }
}
template <int N> DEVI void cp_wait() { asm volatile("cp.async.wait_group %0;" ::"n"(N) : "memory"); }

DEVI int other_chunk(int m, int j) { return m + (m >= j); }
DEVI int p2_col(int n, int j) {
  const int m = n < 18 ? n - 11 : (n - 18) >> 1;
  const int slab = n < 18 ? 1 : 2 + (n & 1);
  return other_chunk(m, j) * 256 + slab * 64;
}

__global__ void __cluster_dims__(2, 1, 1) __launch_bounds__(384, 1)
fused_kernel(const __nv_bfloat16* __restrict__ x, const __nv_bfloat16* __restrict__ wd_re, const __nv_bfloat16* __restrict__ wd_im,
             const __nv_bfloat16* __restrict__ w_r, const __nv_bfloat16* __restrict__ w_gate, const __nv_bfloat16* __restrict__ w_up,
             const __grid_constant__ Maps maps, const __nv_bfloat16* __restrict__ w_down, __nv_bfloat16* __restrict__ out) {
  extern __shared__ __align__(1024) uint8_t smem[];
  const uint32_t rank = blockIdx.x & 1;
  const uint32_t base = smem_u32(smem);
  uint8_t* aux = smem + OFF_AUX;
  const uint32_t auxs = base + OFF_AUX;
  const uint32_t full0 = auxs + OFF_BAR, empty0 = full0 + 8 * STAGES, bar_stat = empty0 + 8 * STAGES, bar_ab = bar_stat + 8,
                 bar_out = bar_ab + 32, bar_pub = bar_out + 64, bar_gu = bar_pub + 16;
  const uint32_t kcur = auxs + OFF_MISC + 16;

  const int tid = threadIdx.x, lane = tid & 31;
  if (tid == 256) TL(0);
  const int cl = blockIdx.x >> 1;
  const int pos = cl - 4 + max(((cl - 29) * 37) >> 8, 0) + ((cl - 4) >> 31 & (7 * cl + 36));
  const int j = (~pos & 3) * 2 + (pos >> 5), part = (pos >> 2) & 1, eb = (((pos >> 3) + (pos >> 5)) & 3) * 2 + rank;
  {
    const uint32_t dst = base + (tid >> 3) * 128 + (((tid ^ (tid >> 3)) & 7) << 4);
    const uint32_t off = (tid >> 3) * (D_ * 2) + (tid & 7) * 16;
    const char* pb = (const char*)x + (off + (uint32_t)j * (256 * D_ * 2));
    const char* pa = (const char*)(part ? wd_im : wd_re) + (off + (uint32_t)eb * (128 * D_ * 2));
    if (tid < 256) {
#pragma unroll
      for (int q = 0; q < 12; q++)
        cp_async16(dst + (q < 8 ? OFF_B + q * 4096 : (q - 8) * 4096), q < 8 ? pb + q * (32 * D_ * 2) : pa + (q - 8) * (32 * D_ * 2));
      asm volatile("cp.async.commit_group;" ::: "memory");
    }
    if (tid == 0) TL(15);
  }
  const int warp = __shfl_sync(0xffffffffu, tid >> 5, 0);
  const int bid = j * 16 + part * 8 + eb;
  const __nv_bfloat16* wd_rows = (bid < 64 ? wd_re : wd_im) + (size_t)(bid & 63) * 16 * D_;
  if (warp == 9) ((uint4*)(aux + OFF_FLAGS))[lane] = make_uint4(0, 0, 0, 0);
  if (tid == 256) {
    prefetch_map(&maps.x);
    prefetch_map(&maps.wd[part]);
    if (base & 1023) __trap();
#pragma unroll
    for (int s = 0; s < STAGES; s++) { mbar_init(full0 + 8 * s, 1); mbar_init(empty0 + 8 * s, 2); }
    mbar_init(bar_stat, 1);
#pragma unroll
    for (int s = 0; s < 4; s++) mbar_init(bar_ab + 8 * s, 4);
    mbar_init(bar_pub, 1);
    mbar_init(bar_pub + 8, 2);
    mbar_init(bar_gu, 1);
    mbar_init(bar_pub + 24, 1);
    sts32(kcur, 0);
    mbar_init(bar_out, 1);
    mbar_init(bar_out + 8, 1);
    asm volatile("fence.mbarrier_init.release.cluster;" ::: "memory");
  }
  __syncthreads();
  asm volatile("barrier.cluster.arrive.relaxed.aligned;" ::: "memory");
  asm volatile("barrier.cluster.wait.acquire.aligned;" ::: "memory");

  if (warp == 8) {
    if (elect_one()) {
      const int arow = eb * 128;
      int pf_i = 0;
      auto prefetch_ws = [&](int k) {
        if ((WS_MASK >> k) & 1) {
          tma_prefetch(&maps.ws_pf[part], pf_i < 2 ? j * 256 + pf_i * 128 : pf_i < 9 ? other_chunk(pf_i - 2, j) * 256 : other_chunk(pf_i - 9, j) * 256 + 128,
                       (j * 8 + eb) * (PR / 8));
          pf_i++;
        }
      };
      auto load_b = [&](int st, const CUtensorMap* m, int col) { tma_load5(base + OFF_B + st * B_BYTES, m, col, j * PR, full0 + 8 * st); };
      TL(1);
#pragma unroll 1
      for (int k = 1; k < K1 + 3; k++) {
        const int st = k & 3;
        mbar_wait(empty0 + 8 * st, ((k >> 2) & 1) ^ 1);
        TKP(2, k);
        if (k < K1) {
          mbar_expect_tx(full0 + 8 * st, A_BYTES + B_BYTES);
          tma_load(base + OFF_B + st * B_BYTES, &maps.x, k * 64, j * 256, full0 + 8 * st);
          tma_load(base + st * A_BYTES, &maps.wd[part], k * 64, arow, full0 + 8 * st);
        } else {
          mbar_expect_tx(full0 + 8 * st, B_BYTES);
          load_b(st, &maps.ws[part], j * 256 + (k - K1) * 64);
        }
        sts32(kcur, k);
        if (k == 4) { prefetch_l2(wd_rows, 16 * D_ * 2); prefetch_map(&maps.ws[part]); prefetch_map(&maps.ws_pf[part]); prefetch_map(&maps.ab_ld); prefetch_map(&maps.ab_st); }
        prefetch_ws(k);
      }
      mbar_wait(bar_stat, 0);
      const uint32_t tag = lds32(auxs + OFF_MISC);
      uint32_t* flags = g_abflag + (eb * 2 + part) * 96;
      mbar_wait(empty0 + 24, 1);
      sts32(kcur, K1 + 3);
      auto put = [&](int h) {
        tma_store(&maps.ab_st, base + h * (A_BYTES / 2), j * 256 + (h >> 1) * 64, part * 1024 + arow + (h & 1) * 64);
        bulk_commit();
      };
#pragma unroll
      for (int w = 1; w >= 0; w--) {
        mbar_wait(bar_ab + 16 * w, 0);
        put(w);
      }
      TL(8);
      TKP(2, K1 + 3);
      mbar_expect_tx(full0 + 24, B_BYTES);
      load_b(3, &maps.ws[part], j * 256 + 192);
      prefetch_ws(K1 + 3);
      bulk_wait<0>();
      TL(11);
      mbar_arrive(bar_pub + 24);
      const uint32_t mirror = auxs + OFF_FLAGS;
      uint32_t mc = 0;
      auto refresh = [&](int lv) {
        cp_async16(mirror + mc + lv * 32, flags + lv * 32);
        cp_async16(mirror + mc + lv * 32 + 16, flags + lv * 32 + 4);
        mc = (mc + 128) & (NMIR * 128 - 1);
      };
      auto ready = [&](int f) {
        uint32_t v[NMIR];
#pragma unroll
        for (int i = 0; i < NMIR; i++) v[i] = lds32(mirror + f * 4 + i * 128);
        bool r = false;
#pragma unroll
        for (int i = 0; i < NMIR; i++) r |= v[i] == tag;
        return r;
      };
      auto level_set = [&](int lv) {
        bool r = false;
#pragma unroll
        for (int i = 0; i < NMIR; i++) {
          const uint4 u = lds128(mirror + i * 128 + lv * 32), v = lds128(mirror + i * 128 + lv * 32 + 16);
          r |= ((u.x ^ tag) | (u.y ^ tag) | (u.z ^ tag) | (u.w ^ tag) | (v.x ^ tag) | (v.y ^ tag) | (v.z ^ tag) | (v.w ^ tag)) == 0;
        }
        return r;
      };
      auto wait_level = [&](int lv) {
        uint32_t it = 0;
        while (!level_set(lv)) {
          refresh(lv);
          if (++it > (1u << 20)) __trap();
          __nanosleep(150);
        }
      };
      auto load_a = [&](int st, uint32_t dst, int col) { tma_load(dst, &maps.ab_ld, col, part * 1024 + arow, full0 + 8 * st); };
      mbar_wait(bar_ab + 8, 0);
      mbar_wait(bar_ab + 24, 0);
      fence_proxy_async_smem();
      refresh(0);
      {
        uint32_t it = 0;
        while (!mbar_test(empty0, 0)) {
          __nanosleep(150);
          refresh(0);
          if (++it > (1u << 20)) __trap();
        }
      }
      uint32_t seen = 0;
      bool ahead = false;
      auto issue_b = [&](int n) {
        TKP(2, K1 + n);
        mbar_expect_tx(full0 + 8 * (n & 3), A_BYTES + B_BYTES);
        load_b(n & 3, &maps.ws[part], other_chunk(n - 4, j) * 256);
      };
      auto try_ahead = [&](int n) {
        if (n < 7 && !ahead && mbar_test(empty0 + 8 * (n - 3), 0)) { issue_b(n + 1); ahead = true; }
      };
#pragma unroll 1
      for (int n = 4; n < 11; n++) {
        const int k = K1 + n, st = k & 3;
        const int c = other_chunk(n - 4, j);
        if (!ahead) {
          mbar_wait(empty0 + 8 * st, ((k >> 2) & 1) ^ 1);
          issue_b(n);
        }
        ahead = false;
        if (n == 4) put(4);
        uint32_t it = 3;
        while (!(seen & 1) && !ready(c)) {
          if ((++it & 3) == 0) refresh(0);
          if (it > (1u << 22)) __trap();
          try_ahead(n);
        }
        if (n == 5) mbar_wait(bar_pub, 0);
        if (n == 6) bulk_wait_read<1>();
        if (n == 7) { bulk_wait<0>(); mbar_arrive(bar_pub + 8); TL(23); }
        TKP(3, k);
        load_a(st, base + st * A_BYTES, c * 256);
        try_ahead(n);
        if (n < 7) put(n + 1);
        sts32(kcur, k);
        seen >>= 1;
        if (n < 9) {
          if (ready(other_chunk(n - 2, j))) seen |= 2;
          else refresh(0);
        }
        if (n == 8) refresh(1);
      }
#pragma unroll 1
      for (int k = K1 + 11; k < KT - 3; k++) {
        const int st = k & 3, col = p2_col(k - K1, j);
        if (k == K1 + 11 || k == K1 + 18) wait_level(k == K1 + 11 ? 1 : 2);
        mbar_wait(empty0 + 8 * st, ((k >> 2) & 1) ^ 1);
        TKP(2, k);
        mbar_expect_tx(full0 + 8 * st, A_BYTES + B_BYTES);
        load_b(st, &maps.ws[part], col);
        load_a(st, base + st * A_BYTES, col);
        sts32(kcur, k);
        if (k == K1 + 15) refresh(2);
        prefetch_ws(k);
        if (k == K1 + 20) { prefetch_map(&maps.ws_h[part]); prefetch_map(&maps.out); }
      }
      const int c1 = p2_col(K2 - 3, j), c2 = p2_col(K2 - 2, j), c3 = c2 + 64;
      auto load_h = [&](int hs, int col, int half, int st) {
        tma_load5(base + OFF_B + hs * (B_BYTES / 2), &maps.ws_h[part], col, j * PR + half * (PR / 2), full0 + 8 * st);
      };
      mbar_wait(empty0 + 8, 0);
      TKP(2, KT - 3);
      mbar_expect_tx(full0 + 8, A_BYTES + B_BYTES);
      load_h(2, c1, 0, 1);
      load_a(1, base + A_BYTES, c1);
      load_a(1, base + OFF_B + 3 * (B_BYTES / 2), c3);
      sts32(kcur, KT - 3);
      wait_out_init(tag);
      mbar_arrive(bar_out + 8);
      mbar_wait(empty0 + 16, 0);
      TKP(2, KT - 2);
      mbar_expect_tx(full0 + 16, A_BYTES + B_BYTES);
      load_h(4, c2, 0, 2);
      load_a(2, base + 2 * A_BYTES, c2);
      load_h(5, c3, 0, 2);
      mbar_wait(empty0 + 24, 0);
      TKP(2, KT - 1);
      mbar_expect_tx(full0 + 24, B_BYTES);
      load_h(6, c1, 1, 3);
      load_h(7, c2, 1, 3);
      mbar_wait(empty0, 1);
      TL(17);
      mbar_expect_tx(full0, B_BYTES / 2);
      load_h(0, c3, 1, 0);
      asm volatile("cp.async.wait_all;" ::: "memory");
    }
  } else if (warp > 8) {
    const int t = tid - 288, w = warp - 9;
    float2* xs = (float2*)(aux + OFF_XS);
    float* red = (float*)(aux + OFF_RED);
    volatile uint32_t* misc = (volatile uint32_t*)(aux + OFF_MISC);

    const uint32_t ring = auxs + OFF_RING + (t >> 5) * 8192 + lane * 16;
    auto fetch_to = [&](uint32_t dst, const __nv_bfloat16* src, auto stepc, bool on) {
      if (on) {
#pragma unroll
        for (int k = 0; k < 4; k++) {
          if (decltype(stepc)::value == 256) cp_async16(dst + k * 512, src + k * 256);
          else cp_async16_once(dst + k * 512, src + k * decltype(stepc)::value);
        }
      }
      asm volatile("cp.async.commit_group;" ::: "memory");
    };
    auto fetch = [&](int slot, const __nv_bfloat16* src, auto stepc, bool on) { fetch_to(ring + slot * 2048, src, stepc, on); };
    const int nrow = w ? 5 : 6, lrow0 = w ? 1 + 5 * w : 0;
    const int row0 = bid * 16 + lrow0;
    const __nv_bfloat16* xrow = x + (size_t)row0 * D_ + lane * 8;
    const __nv_bfloat16* wrow = wd_rows + lrow0 * D_ + lane * 8;
    const int slot4 = (OFF_XS - OFF_RING) / 2048 - 4 * w + (w ? w - 1 : 2);
    auto pace = [&](int k) {
      uint32_t it = 0;
      while ((int)lds32(kcur) < k) {
        if (++it > (1u << 20)) __trap();
        __nanosleep(50);
      }
    };
    auto fetch_row = [&](const __nv_bfloat16* p, int i) { fetch(i < 4 ? i : slot4 + i - 4, p + i * D_, IC<256>{}, i < nrow); };
    auto load_row = [&](int i, uint32_t (&xv)[16]) {
      const uint32_t a = ring + (i < 4 ? i : slot4 + i - 4) * 2048;
#pragma unroll
      for (int k = 0; k < 4; k++) {
        const uint4 v = lds128(a + k * 512);
        xv[4 * k] = v.x; xv[4 * k + 1] = v.y; xv[4 * k + 2] = v.z; xv[4 * k + 3] = v.w;
      }
    };
    mbar_wait(full0, 0);
#pragma unroll
    for (int i = 0; i < 3; i++) fetch_row(xrow, i);
    const uint32_t tag = (ld_relaxed(&g_ctr) & ~(uint32_t)(NCTA - 1)) + NCTA;
    const uint32_t tag16 = (tag >> 7) & 0xffffu, tag5 = (tag16 & 31u) << 11;
    uint32_t xo[6][16];
    auto store_row = [&](int i) {
#pragma unroll
      for (int k = 0; k < 4; k++)
        *(uint4*)(out + (size_t)(row0 + i) * D_ + lane * 8 + k * 256) = make_uint4(xo[i][4 * k], xo[i][4 * k + 1], xo[i][4 * k + 2], xo[i][4 * k + 3]);
    };
    {
      uint4 wv4[4];
#pragma unroll
      for (int k = 0; k < 4; k++) wv4[k] = __ldg((const uint4*)(w_r + lane * 8 + k * 256));
      float sh[8];
      const int ri = nrow - 1 - (lane & 7);
      float wr[32];
      float wrsum = 0.f;
#pragma unroll
      for (int k = 0; k < 4; k++) {
        const uint32_t wv[4] = {wv4[k].x, wv4[k].y, wv4[k].z, wv4[k].w};
#pragma unroll
        for (int c = 0; c < 4; c++) {
          wr[8 * k + 2 * c] = bf_lo(wv[c]);
          wr[8 * k + 2 * c + 1] = bf_hi(wv[c]);
          wrsum += wr[8 * k + 2 * c] + wr[8 * k + 2 * c + 1];
        }
      }
      wrsum = warp_sum(wrsum);
#pragma unroll
      for (int q = 0; q < 8; q++) sh[q] = 0.f;
#pragma unroll 1
      for (int i = 0; i < nrow; i++) {
        uint32_t xv[16];
        if (i + 3 < nrow) pace(LN_K0 + i);
        fetch_row(xrow, i + 3);
        cp_wait<3>();
        load_row(i, xv);
        float s0 = 0.f, s1 = 0.f, q0 = 0.f, q1 = 0.f, r0 = 0.f, r1 = 0.f;
#pragma unroll
        for (int c = 0; c < 16; c++) {
          const float a = bf_lo(xv[c]), b = bf_hi(xv[c]);
          s0 += a;
          s1 += b;
          q0 = fmaf(a, a, q0);
          q1 = fmaf(b, b, q1);
          r0 = fmaf(a, wr[2 * c], r0);
          r1 = fmaf(b, wr[2 * c + 1], r1);
        }
        float s[4] = {s0 + s1, q0 + q1, r0 + r1, 0.f};
        xreduce<2, 16>(s, lane);
        xreduce<1, 8>(s, lane);
#pragma unroll
        for (int q = 5; q > 0; q--) sh[q] = sh[q - 1];
        sh[0] = s[0];
      }
      xreduce<4, 4>(sh, lane);
      xreduce<2, 2>(sh, lane);
      xreduce<1, 1>(sh, lane);
      const float mean = __shfl_sync(0xffffffffu, sh[0], lane & 7) * (1.f / D_);
      float var = fmaf(-mean, mean, __shfl_sync(0xffffffffu, sh[0], 8 + (lane & 7)) * (1.f / D_));
      const float dot = __shfl_sync(0xffffffffu, sh[0], 16 + (lane & 7));
      if (__any_sync(0xffffffffu, mean * mean > 16.f * var)) {
#pragma unroll 1
        for (int i = 0; i < nrow; i++) {
          uint32_t xv[16];
          load_row(i, xv);
          const float m = __shfl_sync(0xffffffffu, mean, nrow - 1 - i);
          float qq = 0.f;
#pragma unroll
          for (int c = 0; c < 16; c++) {
            const float a = bf_lo(xv[c]) - m, b = bf_hi(xv[c]) - m;
            qq = fmaf(a, a, fmaf(b, b, qq));
          }
          qq = warp_sum(qq) * (1.f / D_);
          if (ri == i) var = qq;
        }
      }
      const float mb = bf_round(mean);
      const float den = bf_round(sqrt_approx(bf_round(bf_round(var) + 1e-5f)));
      const float inv = rcp_approx(den);
      if (lane < nrow) st_rec(g_stat + row0 + ri, __float_as_uint(inv), __float_as_uint(mb) | tag16);
      const uint32_t u = pack_bf16(0.f, fmaf(-mb, wrsum, dot) * inv);
      const uint32_t key = lane < nrow ? ((u ^ (0x80000000u | (uint32_t)((int32_t)u >> 31))) & 0xffff0000u) | tag5 | (uint32_t)(S_ - 1 - row0 - ri) : 0u;
      const uint32_t k0 = __reduce_max_sync(0xffffffffu, key);
      const uint32_t k1 = __reduce_max_sync(0xffffffffu, key == k0 ? 0u : key);
      if (lane == 0) { st_rec(g_cand + bid * 3 + w, k0, k1); TL(26 + w); }
      const uint32_t mi = pack_bf16(mb, inv);
      uint32_t mv[6];
#pragma unroll
      for (int i = 0; i < 6; i++) mv[i] = __shfl_sync(0xffffffffu, mi, nrow - 1 - i);
#pragma unroll
      for (int i = 0; i < 6; i++) load_row(min(i, nrow - 1), xo[i]);
#pragma unroll
      for (int i = 0; i < 6; i++) fetch_row(wrow, i);
#pragma unroll
      for (int i = 0; i < 6; i++) {
        const uint32_t mb2 = __byte_perm(mv[i], 0, 0x1010), inv2 = __byte_perm(mv[i], 0, 0x3232);
#pragma unroll
        for (int c = 0; c < 16; c++) xo[i][c] = bf2_fma(bf2_sub(xo[i][c], mb2), inv2, xo[i][c]);
        if (i < 3) store_row(i);
      }
      if (t == 0) TL(16);
#pragma unroll
      for (int q = 0; q < 8; q++) sh[q] = 0.f;
#pragma unroll 1
      for (int i0 = 0; i0 < 6; i0 += 2) {
        uint32_t xv[2][16];
        cp_wait<4>();
        asm volatile("cp.async.commit_group;\ncp.async.commit_group;" ::: "memory");
        load_row(i0, xv[0]);
        load_row(min(i0 + 1, nrow - 1), xv[1]);
        float s0 = 0.f, s1 = 0.f, s2 = 0.f, s3 = 0.f;
#pragma unroll
        for (int c = 0; c < 16; c++) { s0 += bf_lo(xv[0][c]); s1 += bf_hi(xv[0][c]); s2 += bf_lo(xv[1][c]); s3 += bf_hi(xv[1][c]); }
#pragma unroll
        for (int q = 5; q > 1; q--) sh[q] = sh[q - 2];
        sh[1] = s0 + s1;
        sh[0] = s2 + s3;
      }
      xreduce<4, 4>(sh, lane);
      xreduce<2, 2>(sh, lane);
      xreduce<1, 1>(sh, lane);
      sh[0] += __shfl_xor_sync(0xffffffffu, sh[0], 8);
      sh[0] += __shfl_xor_sync(0xffffffffu, sh[0], 16);
      if (lane < 6 && 5 - lane < nrow) st_rec(g_wsum + row0 + 5 - lane, __float_as_uint(sh[0]), tag);
    }
    const int nblk = bid < NFFN ? (w ? (32 - NB0) / 2 : NB0) : 0, blk0 = w ? NB0 + (w - 1) * ((32 - NB0) / 2) : 0;
    if (t == 0) TL(2);
    const size_t guoff = (size_t)(rank * 512 + 16 * blk0 + (lane >> 3)) * F_ + (bid >> 1) * 64 + (lane & 7) * 8;
    const __nv_bfloat16 *pg = w_gate + guoff, *pu = w_up + guoff;
    auto fill = [&]() {
      pace(GU_KF);
      fetch(0, pg, IC<4 * F_>{}, nblk);
      fetch(1, pu, IC<4 * F_>{}, nblk);
      fetch(2, pg + 16 * F_, IC<4 * F_>{}, nblk);
      fetch(3, pu + 16 * F_, IC<4 * F_>{}, nblk);
      store_row(3);
      store_row(4);
      if (w == 0) store_row(5);
    };
    if (w == 0) {
      uint4 cs[4], ws[2];
      uint32_t it = 0, bad;
      auto load_ws = [&]() {
#pragma unroll
        for (int i = 0; i < 2; i++) ws[i] = ld_rec2(g_wsum + part * 1024 + eb * 128 + 2 * lane + 64 * i);
      };
      do {
#pragma unroll
        for (int i = 0; i < 4; i++) cs[i] = ld_rec2(g_stat + j * 256 + 2 * lane + 64 * i);
        bad = 0;
#pragma unroll
        for (int i = 0; i < 4; i++) bad |= ((cs[i].y ^ tag16) | (cs[i].w ^ tag16)) & 0xffffu;
      } while (poll_again(bad, it));
      load_ws();
      const uint32_t sg = (uint32_t)part << 31;
#pragma unroll
      for (int i = 0; i < 4; i++) {
        const uint32_t lo = ((cs[i].x + 0x8000u) ^ sg) >> 16;
        ((uint32_t*)(aux + OFF_COLSTAT))[32 * i + (lane & 16) + (lane & 3) * 4 + ((lane >> 2) & 3)] =
            (((uint32_t)max((int)(cs[i].z - lo + 0x8000u), 0) & 0xffff0000u) | lo) ^ sg;
        const uint32_t m0 = __byte_perm(cs[i].y, 0, 0x3232), m1 = __byte_perm(cs[i].w, 0, 0x3232);
        ((uint4*)(aux + OFF_MEAN))[64 * i + 2 * lane] = make_uint4(m0, m0, m0, m0);
        ((uint4*)(aux + OFF_MEAN))[64 * i + 2 * lane + 1] = make_uint4(m1, m1, m1, m1);
      }
      if (lane == 0) misc[0] = tag;
      while (poll_again((ws[0].y ^ tag) | (ws[0].w ^ tag) | (ws[1].y ^ tag) | (ws[1].w ^ tag), it)) load_ws();
#pragma unroll
      for (int i = 0; i < 2; i++) {
        uint32_t f[4];
#pragma unroll
        for (int h = 0; h < 2; h++) {
          const float wv = -__uint_as_float(h ? ws[i].z : ws[i].x), hi = bf_round(wv), mid = bf_round(wv - hi);
          f[2 * h] = pack_bf16(hi, mid);
          f[2 * h + 1] = pack_bf16(wv - hi - mid, 0.f);
        }
        ((uint4*)(aux + OFF_WSUM))[lane + 32 * i] = make_uint4(f[0], f[1], f[2], f[3]);
      }
      fence_proxy_async_smem();
      __syncwarp();
      if (lane == 0) { mbar_arrive(bar_stat); TL(3); }
      fill();
    } else {
      uint4 kv[6];
      uint32_t it = 0, bad;
      do {
        bad = 0;
#pragma unroll
        for (int i = 0; i < 6; i++) kv[i] = ld_rec2(g_cand + 2 * lane + 64 * i);
#pragma unroll
        for (int i = 0; i < 6; i++) bad |= (kv[i].x ^ tag5) | (kv[i].z ^ tag5);
      } while (poll_again(bad & 0xf800u, it));
      uint32_t k0 = 0, k1 = 0;
#pragma unroll
      for (int i = 0; i < 6; i++) {
        const uint32_t c0 = max(kv[i].x, kv[i].z), c1 = max(min(kv[i].x, kv[i].z), max(kv[i].y, kv[i].w));
        k1 = max(max(k1, c1), min(k0, c0));
        k0 = max(k0, c0);
      }
      const uint32_t m0 = __reduce_max_sync(0xffffffffu, k0);
      const uint32_t m1 = __reduce_max_sync(0xffffffffu, k0 == m0 ? k1 : k0);
      if (t == 32) { misc[2] = m0; misc[3] = m1; }
      {
        const int r0 = S_ - 1 - (m0 & (S_ - 1)), r1 = S_ - 1 - (m1 & (S_ - 1));
        const uint32_t* pa = (const uint32_t*)(x + (size_t)r0 * D_ + rank * 512 + (w - 1) * 256) + lane;
        const uint32_t* pb = (const uint32_t*)(x + (size_t)r1 * D_ + rank * 512 + (w - 1) * 256) + lane;
        uint32_t xa[4], xb[4];
#pragma unroll
        for (int k = 0; k < 4; k++) { xa[k] = ld_relaxed(pa + 32 * k); xb[k] = ld_relaxed(pb + 32 * k); }
        uint2 sa = ld_rec(g_stat + r0), sb = ld_rec(g_stat + r1);
        fill();
        while (poll_again(((sa.y ^ tag16) | (sb.y ^ tag16)) & 0xffffu, it)) {
          sa = ld_rec(g_stat + r0);
          sb = ld_rec(g_stat + r1);
        }
        const uint32_t ma = __byte_perm(sa.y, 0, 0x3232), mb = __byte_perm(sb.y, 0, 0x3232);
        const float ia = __uint_as_float(sa.x), ib = __uint_as_float(sb.x);
#pragma unroll
        for (int k = 0; k < 4; k++) {
          const uint32_t da = bf2_sub(xa[k], ma), db = bf2_sub(xb[k], mb);
          const uint32_t na = pack_bf16(bf_lo(da) * ia, bf_hi(da) * ia), nb = pack_bf16(bf_lo(db) * ib, bf_hi(db) * ib);
          ((float4*)xs)[(w - 1) * 128 + 32 * k + lane] = make_float4(bf_lo(na), bf_lo(nb), bf_hi(na), bf_hi(nb));
        }
      }
    }
    named_bar(1, 96);
    if (t == 0) TL(4);
    if (t == 32) {
      mbar_wait(bar_ab + 8, 0);
      mbar_wait(bar_ab + 24, 0);
      fence_proxy_async_smem();
      tma_store(&maps.ab_ld, base + A_BYTES, j * 256 + 64, part * 1024 + eb * 128);
      bulk_commit();
      mbar_arrive_cluster(bar_pub + 8, rank ^ 1);
      bulk_wait<0>();
      mbar_arrive(bar_pub);
    }
    if (t == 0) {
      auto flag = [&](int lv) {
        fence_gpu();
        st_relaxed(g_abflag + (eb * 2 + part) * 96 + lv * 32 + j, tag);
      };
      mbar_wait(bar_pub + 24, 0);
      flag(0);
      TL(9);
      mbar_wait(bar_pub, 0);
      flag(1);
      asm volatile("red.relaxed.gpu.global.add.u32 [%0], 1;" ::"l"(&g_ctr) : "memory");
      TL(19);
      mbar_wait(bar_pub + 8, 0);
      flag(2);
      TL(22);
    }
    __syncwarp();
    const int cb = bid & 15, kg = bid >> 4;
    const int ndn = w ? 9 : 10;
    const __nv_bfloat16* pd = w_down + (size_t)(kg * 448 + 16 * w + (lane >> 3)) * D_ + cb * 64 + (lane & 7) * 8;
    uint32_t sa = ring;
    uint4 v0[4], v1[4];
    float2 xv[4] = {};
    auto take = [&](uint4 (&v)[4]) {
      cp_wait<3>();
#pragma unroll
      for (int i = 0; i < 4; i++) v[i] = lds128(sa + i * 512);
    };
    auto next_down = [&](bool on) {
      fetch_to(sa, pd, IC<4 * D_>{}, on);
      pd += 48 * D_;
    };
    auto half = [&](float (&acc)[16], const uint4 (&v)[4], int h) {
      gemv8(acc, v[2 * h], xv[2 * h]);
      gemv8(acc, v[2 * h + 1], xv[2 * h + 1]);
    };
    if (nblk) {
      float ag[16], au[16];
#pragma unroll
      for (int i = 0; i < 16; i++) { ag[i] = 0.f; au[i] = 0.f; }
      const float2* xp = xs + 16 * blk0 + (lane >> 3);
      int kq = 2 * GU_K1;
      auto refill = [&](int kc, const __nv_bfloat16* p, bool gu) {
        if (kc < (kq >> 1)) pace(kq >> 1);
        kq += kq < 2 * GU_K0 ? 2 : 1;
        if (gu) fetch_to(sa, p, IC<4 * F_>{}, true);
        else next_down(true);
        sa = ring + ((sa - ring + 2048) & 8191);
      };
      take(v0);
      xv[0] = xp[0];
      xv[1] = xp[4];
      pg += 32 * F_;
      pu += 32 * F_;
      refill(0, pg, true);
#pragma unroll 1
      for (int b = 0; b < nblk; b++) {
        take(v1);
        int kc = lds32(kcur);
        xv[2] = xp[8];
        xv[3] = xp[12];
        xp += 16;
        pg += 16 * F_;
        half(ag, v0, 0);
        refill(kc, pu, b + 2 < nblk);
        half(ag, v0, 1);
        take(v0);
        kc = lds32(kcur);
        pu += 16 * F_;
        half(au, v1, 0);
        xv[0] = xp[0];
        xv[1] = xp[4];
        refill(kc, pg, b + 3 < nblk);
        half(au, v1, 1);
      }
      float s[32];
#pragma unroll
      for (int i = 0; i < 16; i++) { s[i] = ag[i]; s[16 + i] = au[i]; }
      xreduce<16, 16>(s, lane);
      xreduce<8, 8>(s, lane);
      mbar_wait(bar_pub + 8, 0);
      const uint32_t dst = mapa(auxs + OFF_GU + (rank * 3 + w) * 512 + (lane >> 4) * 256 + (lane & 3) * 64 + (lane & 8) * 4, (lane >> 2) & 1);
      const uint32_t dbar = mapa(bar_gu, (lane >> 2) & 1);
      st_async4(dst, s[0], s[1], s[2], s[3], dbar);
      st_async4(dst + 16, s[4], s[5], s[6], s[7], dbar);
      if (w == 0) {
        if (lane == 0) mbar_expect_tx(bar_gu, 6 * 512);
        mbar_wait(bar_gu, 0);
        const float2* r2 = (const float2*)(aux + OFF_GU) + lane;
        float2 g2 = r2[0], u2 = r2[32];
#pragma unroll
        for (int q = 1; q < 6; q++) {
          const float2 a = r2[64 * q], c = r2[64 * q + 32];
          g2.x += a.x; g2.y += a.y; u2.x += c.x; u2.y += c.y;
        }
        float hv[2];
#pragma unroll
        for (int tok = 0; tok < 2; tok++) {
          const float g = bf_round(tok ? g2.y : g2.x), u = bf_round(tok ? u2.y : u2.x);
          hv[tok] = bf_round(__fdividef(g, 1.f + __expf(-g))) * u;
        }
        st_rec(g_h + bid * 32 + lane, pack_bf16(hv[0], hv[1]), tag);
        if (lane == 0) TL(5);
      }
    } else {
#pragma unroll
      for (int u = 0; u < 4; u++) fetch(u, pd + u * 48 * D_, IC<4 * D_>{}, true);
      pd += 4 * 48 * D_;
      take(v0);
      next_down(true);
      sa += 2048;
      pace(H_K);
    }
    if (t == 64) prefetch_l2(out + (size_t)bid * 16 * D_, 16 * D_ * 2);
    if (t == 32) wait_out_init(tag);
    named_bar(1, 96);
    {
      uint4 hv[3];
      uint32_t it = 0;
      bool bad[3] = {true, true, w == 0};
      while (true) {
#pragma unroll
        for (int i = 0; i < 3; i++) if (bad[i]) hv[i] = ld_rec2(g_h + kg * 448 + 2 * (t + 96 * i));
#pragma unroll
        for (int i = 0; i < 3; i++) bad[i] = bad[i] && (hv[i].y != tag || hv[i].w != tag);
        if (!poll_again(bad[0] || bad[1] || bad[2], it)) break;
        __nanosleep(100);
      }
#pragma unroll
      for (int i = 0; i < 3; i++) {
        if (t + 96 * i < 224) ((float4*)xs)[t + 96 * i] = make_float4(bf_lo(hv[i].x), bf_hi(hv[i].x), bf_lo(hv[i].z), bf_hi(hv[i].z));
      }
    }
    named_bar(1, 96);
    if (t == 0) TL(10);
    {
      float ay[16];
#pragma unroll
      for (int q = 0; q < 16; q++) ay[q] = 0.f;
      const float2* hp = xs + 16 * w + (lane >> 3);
      xv[0] = hp[0];
      xv[1] = hp[4];
      auto unit = [&](const uint4 (&v)[4], uint4 (&vn)[4], int u) {
        take(vn);
        xv[2] = hp[8];
        xv[3] = hp[12];
        hp += 48;
        half(ay, v, 0);
        xv[0] = hp[0];
        xv[1] = hp[4];
        next_down(u + 5 < ndn);
        sa = ring + ((sa - ring + 2048) & 8191);
        half(ay, v, 1);
      };
#pragma unroll 1
      for (int u = 0; u < ndn; u += 2) {
        unit(v0, v1, u);
        if (u + 1 < ndn) unit(v1, v0, u + 1);
      }
      xreduce<8, 16>(ay, lane);
      xreduce<4, 8>(ay, lane);
      ((float4*)red)[w * 32 + (lane & 7) * 4 + (lane >> 3)] = make_float4(ay[0], ay[1], ay[2], ay[3]);
    }
    named_bar(1, 96);
    if (t < 64) {
      const float* r = red + 4 * lane + w;
      const uint32_t key = misc[2 + w];
      const uint32_t rb = (key ^ (0x80000000u | ~(uint32_t)((int32_t)key >> 31))) & 0xffff0000u;
      const float gate = bf_round(__fdividef(1.f, 1.f + __expf(-__uint_as_float(rb))));
      const uint32_t v = pack_bf16((r[0] + r[128] + r[256]) * gate, (r[2] + r[130] + r[258]) * gate);
      asm volatile("red.relaxed.gpu.global.add.noftz.bf16x2 [%0], %1;"
                   ::"l"(out + (size_t)(S_ - 1 - (key & (S_ - 1))) * D_ + cb * 64 + 2 * lane), "r"(v) : "memory");
      if (t == 0) TL(6);
    }
  } else {
    float acc[128];
    const int wg = warp >> 2, wi = warp & 3;
    const bool elect = (tid & 127) == 0;
    const uint32_t a_base = base + wg * (A_BYTES / 2);

    auto release = [&](int k) {
      if (elect) mbar_arrive(empty0 + 8 * (k & 3));
    };
    auto mma_step = [&](int st, int scale_d) {
      const uint64_t da = make_desc(a_base + st * A_BYTES), db = make_desc(base + OFF_B + st * B_BYTES);
      wgmma_fence();
      wgmma_n256(acc, da, db, scale_d);
      wgmma_n256(acc, da + 2, db + 2, 1);
      wgmma_n256(acc, da + 4, db + 4, 1);
      wgmma_commit();
      wgmma_n256(acc, da + 6, db + 6, 1);
      wgmma_commit();
    };
    auto stamp = [&](int k) {
      if (elect) TK(wg, k);
    };

#pragma unroll 1
    for (int k = 0; k < K1; k++) {
      if (k == 0) {
        cp_wait<0>();
        fence_proxy_async_smem();
        named_bar(4, 256);
        if (tid == 0) mbar_arrive(full0);
        stamp(k);
      } else {
        stamp(k);
        mbar_wait(full0 + 8 * (k & 3), (k >> 2) & 1);
        TKC(k);
      }
      mma_step(k & 3, k);
      wgmma_wait<2>();
      if (k) release(k - 1);
    }
    {
      mbar_wait(bar_stat, 0);
      uint32_t af[2];
#pragma unroll
      for (int h = 0; h < 2; h++) {
        af[h] = lds32(auxs + OFF_WSUM + (wg * 64 + wi * 16 + h * 8 + (lane >> 2)) * 8 + (lane & 1) * 4);
        if (lane & 2) af[h] = 0;
      }
      wgmma_fence();
      wgmma_n256_rs(acc, af[0], af[1], 0u, 0u, (uint64_t)(((auxs + OFF_MEAN) & 0x3FFFF) >> 4) | ((uint64_t)8 << 32));
      wgmma_commit();
      const uint32_t dst = __shfl_sync(0xffffffffu, a_base + (wi * 16 + (lane & 15)) * 128 + (((lane >> 4) ^ (lane & 7)) << 4), lane);
      const uint32_t cst = auxs + OFF_COLSTAT + (lane & 3) * 16;
      uint4 cn[8];
#pragma unroll
      for (int p = 0; p < 4; p++) cn[p] = lds128(cst + p * 64);
      mbar_wait(full0, 0);
      wgmma_wait<1>();
      release(K1 - 1);
      wgmma_wait<0>();
      if (elect) TL(12 + wg);
#pragma unroll
      for (int p = 0; p < 16; p++) {
        const uint32_t c0 = p & 1 ? cn[p >> 1].z : cn[p >> 1].x, c1 = p & 1 ? cn[p >> 1].w : cn[p >> 1].y;
        const float4 c = make_float4(bf_lo(c0), __uint_as_float(c0), bf_lo(c1), __uint_as_float(c1));
        stmatrix_x4((dst ^ ((p & 3) << 5)) + (p >> 2) * A_BYTES, pack_bf16(acc[8 * p] * c.x, acc[8 * p + 1] * c.y),
                    pack_bf16(acc[8 * p + 2] * c.x, acc[8 * p + 3] * c.y), pack_bf16(acc[8 * p + 4] * c.z, acc[8 * p + 5] * c.w),
                    pack_bf16(acc[8 * p + 6] * c.z, acc[8 * p + 7] * c.w));
        if (p == 3 || p == 15) {
          if (p == 3) fence_proxy_async_smem();
          __syncwarp();
          if (lane == 0) mbar_arrive(bar_ab + 16 * wg + (p & 8));
        }
        if (p == 3) {
#pragma unroll
          for (int q = 4; q < 8; q++) cn[q] = lds128(cst + q * 64);
        }
      }
      named_bar(2 + wg, 128);
      if (elect) TL(29 + wg);
    }
#pragma unroll
    for (int i = 0; i < 128; i++) asm volatile("" : "=f"(acc[i]));
    stamp(K1);
    mma_step(0, 0);
    mbar_wait(bar_ab + 16 * wg + 8, 0);
    fence_proxy_async_smem();
#pragma unroll 1
    for (int k = K1 + 1; k < KT - 4; k++) {
      const bool early = k == K1 + 4;
      if (early) {
        wgmma_wait<0>();
        release(k - 1);
      }
      stamp(k);
      mbar_wait(full0 + 8 * (k & 3), (k >> 2) & 1);
      TKC(k);
      mma_step(k & 3, 1);
      wgmma_wait<2>();
      if (!early) release(k - 1);
    }
    const bool second = wg == 0;
    auto turn = [&](auto oc, uint32_t a, int hs) {
      const uint64_t da = make_desc(a), db = make_desc(base + OFF_B + hs * (B_BYTES / 2));
      wgmma_fence();
#pragma unroll
      for (int q = 0; q < 4; q++) wgmma_n128<decltype(oc)::value>(acc, da + 2 * q, db + 2 * q);
      wgmma_commit();
    };
    const uint32_t a3 = base + OFF_B + 3 * (B_BYTES / 2) + wg * (A_BYTES / 2);
    const uint32_t o0 = ((lane >> 4) * 8 + (lane & 7)) * 128 + (((2 * wi + ((lane >> 3) & 1)) ^ (lane & 7)) << 4);
    auto send = [&](auto oc, uint32_t dst, uint32_t pitch) {
      constexpr int O = decltype(oc)::value;
#pragma unroll
      for (int h = 0; h < 2; h++) {
#pragma unroll
        for (int p = 0; p < 4; p++) {
          const float* v = acc + O + 32 * h + 8 * p;
          stmatrix_x4_t(dst + h * pitch + o0 + p * 2048, pack_bf16(v[0], v[1]), pack_bf16(v[2], v[3]), pack_bf16(v[4], v[5]), pack_bf16(v[6], v[7]));
        }
        fence_proxy_async_smem();
        named_bar(2 + wg, 128);
        if (elect) {
          tma_red_add(&maps.out, dst + h * pitch, eb * 128 + wg * 64, (j * 4 + O / 32 + h) * (PR / 4));
          if (h == 0) TL(24 + (O / 32) + second + 9);
        }
        __syncwarp();
      }
    };
    const float one = __uint_as_float(__shfl_sync(0xffffffffu, lds32(kcur) >> 8, 0) | 0x3f800000u);
    auto cut = [&](int lo) {
#pragma unroll
      for (int i = lo; i < lo + 64; i++) acc[i] *= one;
    };
    mbar_wait(full0, 1);
    wgmma_wait<0>();
    release(KT - 5);
    cut(0);
    if (second) {
      mbar_wait(full0 + 8, 1);
      mbar_wait(full0 + 16, 1);
      named_bar(4, 256);
    }
    stamp(KT - 4);
    turn(IC<0>{}, a_base, 0);
    if (!second) mbar_wait(full0 + 8, 1);
    turn(IC<0>{}, a_base + A_BYTES, 2);
    if (!second) mbar_wait(full0 + 16, 1);
    turn(IC<0>{}, a_base + 2 * A_BYTES, 4);
    wgmma_wait<2>();
    release(0);
    turn(IC<0>{}, a3, 5);
    named_arrive(4 + second, 256);
    stamp(KT - 3);
    if (elect) {
      mbar_wait(bar_out + 8, 0);
      fence_proxy_async();
    }
    __syncwarp();
    mbar_wait(second ? bar_out : empty0 + 24, 0);
    wgmma_wait<2>();
    if (second) named_bar(2 + wg, 128);
    wgmma_wait<0>();
    if (elect && !second) mbar_arrive(bar_out);
    if (elect) TL(24 + second);
    send(IC<0>{}, second ? base + OFF_B + B_BYTES : base + 3 * A_BYTES, A_BYTES / 2);
    cut(64);
    mbar_wait(full0 + 24, 1);
    if (second) mbar_wait(full0, 0);
    named_bar(5 + second, 256);
    stamp(KT - 2);
    turn(IC<64>{}, a_base, 1);
    turn(IC<64>{}, a_base + A_BYTES, 6);
    turn(IC<64>{}, a_base + 2 * A_BYTES, 7);
    if (!second) mbar_wait(full0, 0);
    turn(IC<64>{}, a3, 0);
    if (!second) named_arrive(6, 256);
    stamp(KT - 1);
    wgmma_wait<2>();
    named_bar(2 + wg, 128);
    wgmma_wait<0>();
    if (elect) TL(20 + second);
    send(IC<64>{}, a_base, A_BYTES);
    if (elect) {
      bulk_commit();
      bulk_wait_read<0>();
      if (second) TL(18);
    }
  }
}

typedef CUresult (*EncodeFn)(CUtensorMap*, CUtensorMapDataType, cuuint32_t, void*, const cuuint64_t*, const cuuint64_t*, const cuuint32_t*,
                             const cuuint32_t*, CUtensorMapInterleave, CUtensorMapSwizzle, CUtensorMapL2promotion, CUtensorMapFloatOOBfill);

void make_map(EncodeFn enc, CUtensorMap* m, void* ptr, uint64_t rows, uint64_t cols, uint32_t box_rows, CUtensorMapL2promotion promo,
              uint32_t box_cols = 64, CUtensorMapSwizzle sw = CU_TENSOR_MAP_SWIZZLE_128B) {
  cuuint64_t dims[2] = {cols, rows};
  cuuint64_t strides[1] = {cols * 2};
  cuuint32_t box[2] = {box_cols, box_rows};
  cuuint32_t es[2] = {1, 1};
  enc(m, CU_TENSOR_MAP_DATA_TYPE_BFLOAT16, 2, ptr, dims, strides, box, es, CU_TENSOR_MAP_INTERLEAVE_NONE, sw, promo,
      CU_TENSOR_MAP_FLOAT_OOB_FILL_NONE);
}

void make_map5(EncodeFn enc, CUtensorMap* m, void* ptr, uint64_t cols, uint32_t box_rows, uint32_t box_cols, CUtensorMapSwizzle sw) {
  cuuint64_t dims[5] = {cols, 2, 2, PG, 512 / PG};
  cuuint64_t strides[4] = {cols * 2 * 1024, cols * 2 * 512, cols * 2 * (512 / PG), cols * 2};
  cuuint32_t box[5] = {box_cols, 2, 2, PG, box_rows / (4 * PG)};
  cuuint32_t es[5] = {1, 1, 1, 1, 1};
  enc(m, CU_TENSOR_MAP_DATA_TYPE_BFLOAT16, 5, ptr, dims, strides, box, es, CU_TENSOR_MAP_INTERLEAVE_NONE, sw,
      CU_TENSOR_MAP_L2_PROMOTION_L2_128B, CU_TENSOR_MAP_FLOAT_OOB_FILL_NONE);
}

}

extern "C" void kernel_launch(void* const* d_in, const int* in_sizes, int n_in, void* d_out, int out_size) {
  (void)in_sizes; (void)n_in; (void)out_size;
  void* fn = nullptr;
  cudaDriverEntryPointQueryResult qr;
  cudaGetDriverEntryPoint("cuTensorMapEncodeTiled", &fn, cudaEnableDefault, &qr);
  EncodeFn enc = (EncodeFn)fn;
  void* ab = nullptr;
  cudaGetSymbolAddress(&ab, g_ab);
  Maps maps;
  const CUtensorMapL2promotion P256 = CU_TENSOR_MAP_L2_PROMOTION_L2_256B, P128 = CU_TENSOR_MAP_L2_PROMOTION_L2_128B;
  make_map(enc, &maps.x, d_in[0], S_, D_, 256, P256);
  for (int p = 0; p < 2; p++) {
    make_map5(enc, &maps.ws[p], d_in[1 + p], S_, 256, 64, CU_TENSOR_MAP_SWIZZLE_128B);
    make_map5(enc, &maps.ws_h[p], d_in[1 + p], S_, 128, 64, CU_TENSOR_MAP_SWIZZLE_128B);
    make_map5(enc, &maps.ws_pf[p], d_in[1 + p], S_, 32, 128, CU_TENSOR_MAP_SWIZZLE_NONE);
  }
  make_map(enc, &maps.wd[0], d_in[3], D_, D_, 128, P256);
  make_map(enc, &maps.wd[1], d_in[4], D_, D_, 128, P256);
  make_map(enc, &maps.ab_ld, ab, 2 * D_, S_, 128, P128);
  make_map(enc, &maps.ab_st, ab, 2 * D_, S_, 64, P128);
  make_map5(enc, &maps.out, d_out, D_, 64, 64, CU_TENSOR_MAP_SWIZZLE_128B);
  cudaFuncSetAttribute(fused_kernel, cudaFuncAttributeMaxDynamicSharedMemorySize, SMEM_BYTES);
  fused_kernel<<<NCTA, 384, SMEM_BYTES, cudaStreamPerThread>>>(
      (const __nv_bfloat16*)d_in[0], (const __nv_bfloat16*)d_in[3], (const __nv_bfloat16*)d_in[4], (const __nv_bfloat16*)d_in[6],
      (const __nv_bfloat16*)d_in[7], (const __nv_bfloat16*)d_in[8], maps, (const __nv_bfloat16*)d_in[9], (__nv_bfloat16*)d_out);
}
```

```cpp
#include <cuda_runtime.h>
#include <cuda_bf16.h>
#include <cuda.h>
#include <stdint.h>

#define DEVI __device__ __forceinline__

namespace {

constexpr int S_ = 2048, D_ = 1024, F_ = 3584;
constexpr int STAGES = 4;
constexpr int A_BYTES = 128 * 64 * 2, B_BYTES = 256 * 64 * 2;
constexpr int K1 = 16, K2 = 32, KT = K1 + K2;
constexpr int NCTA = 128;
constexpr int NFFN = 112;
constexpr int CP0 = 2;
constexpr int NST = 3;
constexpr int PG = 4;
constexpr int PR = 64 / PG;
constexpr int NMIR = 4;
constexpr int NB0 = 8;
constexpr int LN_K0 = 4;
constexpr int GU_KF = 15;
constexpr int GU_K1 = 22;
constexpr int GU_K0 = 24;
constexpr int H_K = 30;
constexpr unsigned long long WS_MASK = 0xca0003ffc0ull;

constexpr uint32_t SM0 = 1024;
constexpr int OFF_B = STAGES * A_BYTES;
constexpr int OFF_AUX = OFF_B + STAGES * B_BYTES;
constexpr int OFF_RING = 0;
constexpr int OFF_XS = OFF_RING + 3 * 8192;
constexpr int OFF_GU = OFF_XS + 4096;
constexpr int OFF_WSUM = OFF_GU;
constexpr int OFF_STAT = OFF_XS + 8192;
constexpr int OFF_RED = OFF_STAT;
constexpr int OFF_FLAGS = OFF_STAT + 1536;
constexpr int OFF_BAR = OFF_STAT + 2048;
constexpr int OFF_MISC = OFF_BAR + 224;
constexpr int AUX_BYTES = OFF_MISC + 32;
constexpr int SMEM_BYTES = OFF_AUX + AUX_BYTES;
static_assert(SMEM_BYTES <= 232448, "smem");

template <int V> struct IC { static constexpr int value = V; };

struct Maps {
  CUtensorMap x, wd[2], ws[2], ws_h[2], ws_pf[2], ab_ld, ab_st, out;
};

__device__ __nv_bfloat16 g_ab[2 * D_ * S_];
__device__ uint2 g_stat[S_];
__device__ uint2 g_wsum[2 * D_];
__device__ uint2 g_cand[NCTA * 3];
__device__ uint2 g_h[F_];
__device__ __align__(128) uint32_t g_abflag[16 * 3 * 32];
__device__ uint32_t g_ctr;
#define TL(i) do {} while (0)
#define TK(r, k) do {} while (0)

#define TKP(r, k) TK(r, k)
#define TKC(k)
DEVI uint32_t smem_u32(const void* p) { return (uint32_t)__cvta_generic_to_shared(p); }
DEVI void mbar_init(uint32_t bar, uint32_t cnt) { asm volatile("mbarrier.init.shared::cta.b64 [%0], %1;" ::"r"(bar), "r"(cnt) : "memory"); }
DEVI void mbar_expect_tx(uint32_t bar, uint32_t bytes) { asm volatile("mbarrier.arrive.expect_tx.shared::cta.b64 _, [%0], %1;" ::"r"(bar), "r"(bytes) : "memory"); }
DEVI void mbar_arrive(uint32_t bar) { asm volatile("mbarrier.arrive.shared::cta.b64 _, [%0];" ::"r"(bar) : "memory"); }
DEVI void mbar_arrive_cluster(uint32_t bar, uint32_t cta) {
  asm volatile("{\n.reg .b32 ra;\nmapa.shared::cluster.u32 ra, %0, %1;\nmbarrier.arrive.shared::cluster.b64 _, [ra];\n}" ::"r"(bar), "r"(cta) : "memory");
}
DEVI uint32_t mapa(uint32_t a, uint32_t cta) { uint32_t r; asm("mapa.shared::cluster.u32 %0, %1, %2;" : "=r"(r) : "r"(a), "r"(cta)); return r; }
DEVI void st_async4(uint32_t dst, float a, float b, float c, float d, uint32_t bar) {
  asm volatile("st.async.shared::cluster.mbarrier::complete_tx::bytes.v4.f32 [%0], {%1, %2, %3, %4}, [%5];"
               ::"r"(dst), "f"(a), "f"(b), "f"(c), "f"(d), "r"(bar) : "memory");
}
DEVI bool mbar_try_wait(uint32_t bar, uint32_t parity) {
  uint32_t ok;
  asm volatile("{\n.reg .pred p;\nmbarrier.try_wait.parity.shared::cta.b64 p, [%1], %2;\nselp.u32 %0, 1, 0, p;\n}" : "=r"(ok) : "r"(bar), "r"(parity) : "memory");
  return ok;
}
DEVI bool mbar_test(uint32_t bar, uint32_t parity) {
  uint32_t ok;
  asm volatile("{\n.reg .pred p;\nmbarrier.test_wait.parity.shared::cta.b64 p, [%1], %2;\nselp.u32 %0, 1, 0, p;\n}" : "=r"(ok) : "r"(bar), "r"(parity) : "memory");
  return ok;
}
DEVI void mbar_wait(uint32_t bar, uint32_t parity) {
  uint32_t n = 0;
  while (!mbar_try_wait(bar, parity)) { if (++n > (1u << 20)) __trap(); }
}
DEVI void tma_load(uint32_t dst, const CUtensorMap* m, int c0, int c1, uint32_t bar) {
  asm volatile("cp.async.bulk.tensor.2d.shared::cluster.global.mbarrier::complete_tx::bytes [%0], [%1, {%3, %4}], [%2];"
               ::"r"(dst), "l"(m), "r"(bar), "r"(c0), "r"(c1) : "memory");
}
DEVI void tma_load3(uint32_t dst, const CUtensorMap* m, int c0, int c1, int c2, uint32_t bar) {
  asm volatile("cp.async.bulk.tensor.3d.shared::cluster.global.mbarrier::complete_tx::bytes [%0], [%1, {%3, %5, %4}], [%2];"
               ::"r"(dst), "l"(m), "r"(bar), "r"(c0), "r"(c2), "r"(c1) : "memory");
}
DEVI void tma_load5(uint32_t dst, const CUtensorMap* m, int c0, int c4, uint32_t bar) {
  asm volatile("cp.async.bulk.tensor.5d.shared::cluster.global.mbarrier::complete_tx::bytes [%0], [%1, {%3, %5, %5, %5, %4}], [%2];"
               ::"r"(dst), "l"(m), "r"(bar), "r"(c0), "r"(c4), "r"(0) : "memory");
}
DEVI void tma_store(const CUtensorMap* m, uint32_t src, int c0, int c1) {
  asm volatile("cp.async.bulk.tensor.2d.global.shared::cta.bulk_group [%0, {%2, %3}], [%1];" ::"l"(m), "r"(src), "r"(c0), "r"(c1) : "memory");
}
DEVI void tma_red_add(const CUtensorMap* m, uint32_t src, int c0, int c1) {
  asm volatile("cp.reduce.async.bulk.tensor.5d.global.shared::cta.add.bulk_group [%0, {%2, %4, %4, %4, %3}], [%1];" ::"l"(m), "r"(src), "r"(c0), "r"(c1), "r"(0) : "memory");
}
DEVI uint4 lds128(uint32_t a) { uint4 v; asm volatile("ld.shared.v4.u32 {%0,%1,%2,%3}, [%4];" : "=r"(v.x), "=r"(v.y), "=r"(v.z), "=r"(v.w) : "r"(a) : "memory"); return v; }
DEVI uint2 lds64(uint32_t a) { uint2 v; asm volatile("ld.shared.v2.u32 {%0,%1}, [%2];" : "=r"(v.x), "=r"(v.y) : "r"(a) : "memory"); return v; }
DEVI uint32_t lds32(uint32_t a) { uint32_t v; asm volatile("ld.volatile.shared.u32 %0, [%1];" : "=r"(v) : "r"(a) : "memory"); return v; }
DEVI void sts32(uint32_t a, uint32_t v) { asm volatile("st.volatile.shared.u32 [%0], %1;" ::"r"(a), "r"(v) : "memory"); }
DEVI void tma_prefetch(const CUtensorMap* m, int c0, int c1) {
  asm volatile("cp.async.bulk.prefetch.tensor.5d.L2.global [%0, {%1, %3, %3, %3, %2}];" ::"l"(m), "r"(c0), "r"(c1), "r"(0) : "memory");
}
DEVI void cp_async16(uint32_t dst, const void* src) { asm volatile("cp.async.cg.shared.global [%0], [%1], 16;" ::"r"(dst), "l"(src) : "memory"); }
DEVI void cp_async16_once(uint32_t dst, const void* src) {
  asm volatile("{\n.reg .b64 pol;\ncreatepolicy.fractional.L2::evict_first.b64 pol, 1.0;\n"
               "cp.async.cg.shared.global.L2::cache_hint [%0], [%1], 16, pol;\n}" ::"r"(dst), "l"(src) : "memory");
}
DEVI bool elect_one() {
  uint32_t p;
  asm volatile("{\n.reg .pred P;\nelect.sync _|P, 0xffffffff;\nselp.u32 %0, 1, 0, P;\n}" : "=r"(p));
  return p;
}
DEVI float sqrt_approx(float v) { float r; asm("sqrt.approx.ftz.f32 %0, %1;" : "=f"(r) : "f"(v)); return r; }
DEVI float rcp_approx(float v) { float r; asm("rcp.approx.ftz.f32 %0, %1;" : "=f"(r) : "f"(v)); return r; }
DEVI void bulk_commit() { asm volatile("cp.async.bulk.commit_group;" ::: "memory"); }
template <int N> DEVI void bulk_wait() { asm volatile("cp.async.bulk.wait_group %0;" ::"n"(N) : "memory"); }
template <int N> DEVI void bulk_wait_read() { asm volatile("cp.async.bulk.wait_group.read %0;" ::"n"(N) : "memory"); }
DEVI void fence_proxy_async() { asm volatile("fence.proxy.async.global;" ::: "memory"); }
DEVI void fence_proxy_async_smem() { asm volatile("fence.proxy.async.shared::cta;" ::: "memory"); }
DEVI void prefetch_map(const CUtensorMap* m) { asm volatile("prefetch.tensormap [%0];" ::"l"(m) : "memory"); }
DEVI void named_bar(int id, int n) { asm volatile("bar.sync %0, %1;" ::"r"(id), "r"(n) : "memory"); }
DEVI void named_arrive(int id, int n) { asm volatile("bar.arrive %0, %1;" ::"r"(id), "r"(n) : "memory"); }
DEVI void wgmma_fence() { asm volatile("wgmma.fence.sync.aligned;" ::: "memory"); }
DEVI void wgmma_commit() { asm volatile("wgmma.commit_group.sync.aligned;" ::: "memory"); }
template <int N> DEVI void wgmma_wait() { asm volatile("wgmma.wait_group.sync.aligned %0;" ::"n"(N) : "memory"); }
DEVI uint64_t make_desc(uint32_t addr) {
  return (uint64_t)((addr & 0x3FFFF) >> 4) | ((uint64_t)1 << 16) | ((uint64_t)64 << 32) | ((uint64_t)1 << 62);
}
DEVI uint32_t ld_acquire(const uint32_t* p) { uint32_t v; asm volatile("ld.acquire.gpu.global.u32 %0, [%1];" : "=r"(v) : "l"(p) : "memory"); return v; }
DEVI void fence_gpu() { asm volatile("fence.acq_rel.gpu;" ::: "memory"); }
DEVI uint32_t ld_relaxed(const uint32_t* p) { uint32_t v; asm volatile("ld.relaxed.gpu.global.u32 %0, [%1];" : "=r"(v) : "l"(p) : "memory"); return v; }
DEVI void st_rec(uint2* p, uint32_t a, uint32_t b) {
  asm volatile("{\n.reg .b64 t;\nmov.b64 t, {%1, %2};\nst.relaxed.gpu.global.b64 [%0], t;\n}" ::"l"(p), "r"(a), "r"(b) : "memory");
}
DEVI uint4 ld_rec2(const uint2* p) {
  uint4 v;
  asm volatile("{\n.reg .b64 a, b;\nld.relaxed.gpu.global.v2.b64 {a, b}, [%4];\nmov.b64 {%0, %1}, a;\nmov.b64 {%2, %3}, b;\n}"
               : "=r"(v.x), "=r"(v.y), "=r"(v.z), "=r"(v.w) : "l"(p) : "memory");
  return v;
}
DEVI uint2 ld_rec(const uint2* p) {
  uint2 v;
  asm volatile("{\n.reg .b64 a;\nld.relaxed.gpu.global.b64 a, [%2];\nmov.b64 {%0, %1}, a;\n}" : "=r"(v.x), "=r"(v.y) : "l"(p) : "memory");
  return v;
}
DEVI bool poll_again(bool bad, uint32_t& it) {
  if (!__any_sync(0xffffffffu, bad)) return false;
  if (++it > (1u << 18)) __trap();
  __nanosleep(40);
  return true;
}
DEVI void st_relaxed(uint32_t* p, uint32_t v) { asm volatile("st.relaxed.gpu.global.u32 [%0], %1;" ::"l"(p), "r"(v) : "memory"); }
DEVI uint32_t pack_bf16(float lo, float hi) { uint32_t r; asm("cvt.rn.bf16x2.f32 %0, %1, %2;" : "=r"(r) : "f"(hi), "f"(lo)); return r; }
DEVI float bf_lo(uint32_t v) { return __uint_as_float(v << 16); }
DEVI float bf_hi(uint32_t v) { return __uint_as_float(v & 0xffff0000u); }
DEVI float bf_round(float v) { return bf_hi(pack_bf16(0.f, v)); }
DEVI uint32_t bf2_sub(uint32_t a, uint32_t b) { uint32_t r; asm("sub.rn.bf16x2 %0, %1, %2;" : "=r"(r) : "r"(a), "r"(b)); return r; }
DEVI uint32_t bf2_fma(uint32_t a, uint32_t b, uint32_t c) { uint32_t r; asm("fma.rn.bf16x2 %0, %1, %2, %3;" : "=r"(r) : "r"(a), "r"(b), "r"(c)); return r; }
DEVI void prefetch_l2(const void* p, uint32_t bytes) { asm volatile("cp.async.bulk.prefetch.L2.global [%0], %1;" ::"l"(p), "r"(bytes) : "memory"); }
DEVI void stmatrix_x4(uint32_t addr, uint32_t a, uint32_t b, uint32_t c, uint32_t d) {
  asm volatile("stmatrix.sync.aligned.m8n8.x4.shared.b16 [%0], {%1,%2,%3,%4};" ::"r"(addr), "r"(a), "r"(b), "r"(c), "r"(d) : "memory");
}
DEVI void stmatrix_x4_t(uint32_t addr, uint32_t a, uint32_t b, uint32_t c, uint32_t d) {
  asm volatile("stmatrix.sync.aligned.m8n8.x4.trans.shared.b16 [%0], {%1,%2,%3,%4};" ::"r"(addr), "r"(a), "r"(b), "r"(c), "r"(d) : "memory");
}
DEVI void gemv8(float (&acc)[16], const uint4& v, const float2 xv) {
  const uint32_t g4[4] = {v.x, v.y, v.z, v.w};
#pragma unroll
  for (int c = 0; c < 4; c++) {
    const float lo = bf_lo(g4[c]), hi = bf_hi(g4[c]);
    acc[4 * c + 0] = fmaf(lo, xv.x, acc[4 * c + 0]);
    acc[4 * c + 1] = fmaf(lo, xv.y, acc[4 * c + 1]);
    acc[4 * c + 2] = fmaf(hi, xv.x, acc[4 * c + 2]);
    acc[4 * c + 3] = fmaf(hi, xv.y, acc[4 * c + 3]);
  }
}
template <int H, int MASK, int N> DEVI void xreduce(float (&s)[N], int lane) {
  const bool up = lane & MASK;
#pragma unroll
  for (int i = 0; i < H; i++) {
    const float keep = up ? s[i + H] : s[i], send = up ? s[i] : s[i + H];
    s[i] = keep + __shfl_xor_sync(0xffffffffu, send, MASK);
  }
}
DEVI float warp_sum(float v) {
#pragma unroll
  for (int o = 16; o; o >>= 1) v += __shfl_xor_sync(0xffffffffu, v, o);
  return v;
}

#define ACC128 \
      "{%0,%1,%2,%3,%4,%5,%6,%7,%8,%9,%10,%11,%12,%13,%14,%15,%16,%17,%18,%19,%20,%21,%22,%23,%24,%25,%26,%27,%28,%29,%30,%31," \
      "%32,%33,%34,%35,%36,%37,%38,%39,%40,%41,%42,%43,%44,%45,%46,%47,%48,%49,%50,%51,%52,%53,%54,%55,%56,%57,%58,%59,%60,%61,%62,%63," \
      "%64,%65,%66,%67,%68,%69,%70,%71,%72,%73,%74,%75,%76,%77,%78,%79,%80,%81,%82,%83,%84,%85,%86,%87,%88,%89,%90,%91,%92,%93,%94,%95," \
      "%96,%97,%98,%99,%100,%101,%102,%103,%104,%105,%106,%107,%108,%109,%110,%111,%112,%113,%114,%115,%116,%117,%118,%119,%120,%121,%122,%123,%124,%125,%126,%127},"
#define R128(d) R8(d, 0), R8(d, 8), R8(d, 16), R8(d, 24), R8(d, 32), R8(d, 40), R8(d, 48), R8(d, 56), R8(d, 64), R8(d, 72), R8(d, 80), \
                R8(d, 88), R8(d, 96), R8(d, 104), R8(d, 112), R8(d, 120)
#define R8(d, i) "+f"(d[i]), "+f"(d[i + 1]), "+f"(d[i + 2]), "+f"(d[i + 3]), "+f"(d[i + 4]), "+f"(d[i + 5]), "+f"(d[i + 6]), "+f"(d[i + 7])
DEVI void wgmma_n256(float (&d)[128], uint64_t da, uint64_t db, int scale_d) {
  asm volatile("{\n.reg .pred p;\nsetp.ne.b32 p, %130, 0;\nwgmma.mma_async.sync.aligned.m64n256k16.f32.bf16.bf16 " ACC128
               " %128, %129, p, 1, 1, 0, 0;\n}\n" : R128(d) : "l"(da), "l"(db), "r"(scale_d));
}
DEVI void wgmma_n256_rs(float (&d)[128], uint32_t a0, uint32_t a1, uint32_t a2, uint32_t a3, uint64_t db) {
  asm volatile("wgmma.mma_async.sync.aligned.m64n256k16.f32.bf16.bf16 " ACC128 " {%128, %129, %130, %131}, %132, 1, 1, 1, 0;\n"
               : R128(d) : "r"(a0), "r"(a1), "r"(a2), "r"(a3), "l"(db));
}

#define ACC64 \
      "{%0,%1,%2,%3,%4,%5,%6,%7,%8,%9,%10,%11,%12,%13,%14,%15,%16,%17,%18,%19,%20,%21,%22,%23,%24,%25,%26,%27,%28,%29,%30,%31," \
      "%32,%33,%34,%35,%36,%37,%38,%39,%40,%41,%42,%43,%44,%45,%46,%47,%48,%49,%50,%51,%52,%53,%54,%55,%56,%57,%58,%59,%60,%61,%62,%63},"
template <int O> DEVI void wgmma_n128(float (&d)[128], uint64_t da, uint64_t db) {
  asm volatile("wgmma.mma_async.sync.aligned.m64n128k16.f32.bf16.bf16 " ACC64 " %64, %65, 1, 1, 1, 0, 0;\n"
               : R8(d, O), R8(d, O + 8), R8(d, O + 16), R8(d, O + 24), R8(d, O + 32), R8(d, O + 40), R8(d, O + 48), R8(d, O + 56)
               : "l"(da), "l"(db));
}

DEVI void wait_out_init(uint32_t tag) {
  uint32_t it = 0;
  while ((int32_t)(ld_acquire(&g_ctr) - tag) < 0) { if (++it > (1u << 20)) __trap(); }
}
template <int N> DEVI void cp_wait() { asm volatile("cp.async.wait_group %0;" ::"n"(N) : "memory"); }

DEVI int other_chunk(int m, int j) { return m + (m >= j); }
DEVI int p2_col(int n, int j) {
  const int m = n < 18 ? n - 11 : (n - 18) >> 1;
  const int slab = n < 18 ? 1 : 2 + (n & 1);
  return other_chunk(m, j) * 256 + slab * 64;
}

__global__ void __cluster_dims__(2, 1, 1) __launch_bounds__(384, 1)
fused_kernel(const __nv_bfloat16* __restrict__ x, const __nv_bfloat16* __restrict__ wd_re, const __nv_bfloat16* __restrict__ wd_im,
             const __nv_bfloat16* __restrict__ w_r, const __nv_bfloat16* __restrict__ w_gate, const __nv_bfloat16* __restrict__ w_up,
             const __grid_constant__ Maps maps, const __nv_bfloat16* __restrict__ w_down, __nv_bfloat16* __restrict__ out) {
  extern __shared__ __align__(1024) uint8_t smem[];
  const uint32_t rank = blockIdx.x & 1;
  const uint32_t base = smem_u32(smem);
  uint8_t* aux = smem + OFF_AUX;
  const uint32_t auxs = base + OFF_AUX;
  const uint32_t full0 = auxs + OFF_BAR, empty0 = full0 + 8 * STAGES, bar_stat = empty0 + 8 * STAGES, bar_ab = bar_stat + 8,
                 bar_out = bar_ab + 32, bar_pub = bar_out + 64, bar_gu = bar_pub + 16;
  const uint32_t kcur = auxs + OFF_MISC + 16;

  const int tid = threadIdx.x, lane = tid & 31;
  if (tid == 256) TL(0);
  const int cl = blockIdx.x >> 1;
  const int pos = cl - 4 + max(((cl - 29) * 37) >> 8, 0) + ((cl - 4) >> 31 & (7 * cl + 36));
  const int j = (~pos & 3) * 2 + (pos >> 5), half = (pos >> 2) & 1, eb = (((pos >> 3) + (pos >> 5)) & 3) * 2 + rank;
  {
    const uint32_t dst = base + (tid >> 3) * 128 + (((tid ^ (tid >> 3)) & 7) << 4);
    const char* pa = (const char*)x + (uint32_t)((half * 1024 + j * 64 + (tid >> 3)) * (D_ * 2) + (tid & 7) * 16);
    const uint32_t off = (eb * 64 + (tid >> 4) + (tid & 8) * 64) * (D_ * 2) + (tid & 7) * 16;
    if (tid < 256) {
#pragma unroll
      for (int q = 0; q < 12; q++)
        cp_async16(dst + (q < 4 ? q * 4096 : OFF_B + (q - 4) * 4096),
                   q < 4 ? pa + ((q & 1) * 32 + (q >> 1) * 512) * (D_ * 2) : (const char*)(q < 8 ? wd_re : wd_im) + off + (q & 3) * (16 * D_ * 2));
      asm volatile("cp.async.commit_group;" ::: "memory");
    }
    if (tid == 0) TL(15);
  }
  const int warp = __shfl_sync(0xffffffffu, tid >> 5, 0);
  const int bid = j * 16 + half * 8 + eb;
  const __nv_bfloat16* wd_rows = (bid < 64 ? wd_re : wd_im) + (size_t)(bid & 63) * 16 * D_;
  if (warp == 9) ((uint4*)(aux + OFF_FLAGS))[lane] = make_uint4(0, 0, 0, 0);
  if (tid == 256) {
    prefetch_map(&maps.x);
    prefetch_map(&maps.wd[0]);
    prefetch_map(&maps.wd[1]);
    if (base != (rank << 24) + SM0) __trap();
#pragma unroll
    for (int s = 0; s < STAGES; s++) { mbar_init(full0 + 8 * s, 1); mbar_init(empty0 + 8 * s, 2); }
    mbar_init(bar_stat, 3);
#pragma unroll
    for (int s = 0; s < 4; s++) mbar_init(bar_ab + 8 * s, 4);
    mbar_init(bar_pub, 1);
    mbar_init(bar_pub + 8, 2);
    mbar_init(bar_gu, 1);
    mbar_init(bar_pub + 24, 1);
    sts32(kcur, 0);
    mbar_init(bar_out, 1);
    mbar_init(bar_out + 8, 1);
    asm volatile("fence.mbarrier_init.release.cluster;" ::: "memory");
  }
  __syncthreads();
  asm volatile("barrier.cluster.arrive.relaxed.aligned;" ::: "memory");
  asm volatile("barrier.cluster.wait.acquire.aligned;" ::: "memory");

  if (warp == 8) {
    if (elect_one()) {
      const int arow = eb * 128;
      int pf_i = 0;
      auto prefetch_ws = [&](int k) {
        if ((WS_MASK >> k) & 1) {
          const int q = pf_i < 4 ? pf_i : pf_i < 10 ? pf_i >= 7 : 2 + (pf_i & 1);
          const int c = pf_i < 4 ? j >> 1 : other_chunk(pf_i < 7 ? pf_i - 4 : pf_i < 10 ? pf_i - 7 : (pf_i - 10) >> 1, j >> 1);
          tma_prefetch(&maps.ws_pf[q & 1], half * 1024 + (q & 2) * 256 + c * 128, (j * 8 + eb) * (PR / 8));
          pf_i++;
        }
      };
      auto ws_col = [&](int col) { return half * 1024 + (col & 128) * 4 + (col >> 8) * 64; };
      auto load_b = [&](int st, int col) { tma_load5(base + OFF_B + st * B_BYTES, &maps.ws[(col >> 6) & 1], ws_col(col), j * PR, full0 + 8 * st); };
      TL(1);
#pragma unroll 1
      for (int k = CP0; k < K1 + 2; k++) {
        const int st = k & 3;
        mbar_wait(empty0 + 8 * st, ((k >> 2) & 1) ^ 1);
        TKP(2, k);
        if (k < K1) {
          mbar_expect_tx(full0 + 8 * st, A_BYTES + B_BYTES);
          tma_load3(base + st * A_BYTES, &maps.x, k * 64, j * 64, half * 2, full0 + 8 * st);
          tma_load3(base + OFF_B + st * B_BYTES, &maps.wd[0], k * 64, 0, eb * 64, full0 + 8 * st);
          tma_load3(base + OFF_B + st * B_BYTES + B_BYTES / 2, &maps.wd[1], k * 64, 0, eb * 64, full0 + 8 * st);
        } else {
          mbar_expect_tx(full0 + 8 * st, B_BYTES);
          load_b(st, j * 256 + (k - K1) * 64);
        }
        sts32(kcur, k);
        if (k == 4) { prefetch_l2(wd_rows, 16 * D_ * 2); prefetch_map(&maps.ws[0]); prefetch_map(&maps.ws[1]); prefetch_map(&maps.ws_pf[0]); prefetch_map(&maps.ws_pf[1]); prefetch_map(&maps.ab_ld); prefetch_map(&maps.ab_st); }
        prefetch_ws(k);
      }
      mbar_wait(bar_stat, 0);
      const uint32_t tag = lds32(auxs + OFF_MISC);
      uint32_t* flags = g_abflag + (eb * 2 + half) * 96;
      auto put = [&](int h) {
        tma_store(&maps.ab_st, base + h * (A_BYTES / 2), j * 256 + (h >> 1) * 64, half * 1024 + arow + (h & 1) * 64);
        bulk_commit();
      };
      auto own_b = [&](int q) {
        mbar_wait(empty0 + 8 * q, 1);
        TKP(2, K1 + q);
        sts32(kcur, K1 + q);
        mbar_expect_tx(full0 + 8 * q, B_BYTES);
        load_b(q, j * 256 + q * 64);
      };
      mbar_wait(bar_ab + 8, 0);
      fence_proxy_async_smem();
      put(0);
      mbar_wait(bar_ab, 0);
      put(1);
      TL(8);
      own_b(2);
      bulk_wait<0>();
      TL(11);
      mbar_arrive(bar_pub + 24);
      own_b(3);
      const uint32_t mirror = auxs + OFF_FLAGS;
      uint32_t mc = 0;
      auto refresh = [&](int lv) {
        cp_async16(mirror + mc + lv * 32, flags + lv * 32);
        cp_async16(mirror + mc + lv * 32 + 16, flags + lv * 32 + 4);
        mc = (mc + 128) & (NMIR * 128 - 1);
      };
      auto ready = [&](int f) {
        uint32_t v[NMIR];
#pragma unroll
        for (int i = 0; i < NMIR; i++) v[i] = lds32(mirror + f * 4 + i * 128);
        bool r = false;
#pragma unroll
        for (int i = 0; i < NMIR; i++) r |= v[i] == tag;
        return r;
      };
      auto level_set = [&](int lv) {
        bool r = false;
#pragma unroll
        for (int i = 0; i < NMIR; i++) {
          const uint4 u = lds128(mirror + i * 128 + lv * 32), v = lds128(mirror + i * 128 + lv * 32 + 16);
          r |= ((u.x ^ tag) | (u.y ^ tag) | (u.z ^ tag) | (u.w ^ tag) | (v.x ^ tag) | (v.y ^ tag) | (v.z ^ tag) | (v.w ^ tag)) == 0;
        }
        return r;
      };
      auto wait_level = [&](int lv) {
        uint32_t it = 0;
        while (!level_set(lv)) {
          refresh(lv);
          if (++it > (1u << 20)) __trap();
          __nanosleep(150);
        }
      };
      auto load_a = [&](int st, uint32_t dst, int col) { tma_load(dst, &maps.ab_ld, col, half * 1024 + arow, full0 + 8 * st); };
      mbar_wait(bar_ab + 16, 0);
      mbar_wait(bar_ab + 24, 0);
      fence_proxy_async_smem();
      refresh(0);
      {
        uint32_t it = 0;
        while (!mbar_test(empty0, 0)) {
          __nanosleep(150);
          refresh(0);
          if (++it > (1u << 20)) __trap();
        }
      }
      uint32_t seen = 0;
      bool ahead = false;
      auto issue_b = [&](int n) {
        TKP(2, K1 + n);
        mbar_expect_tx(full0 + 8 * (n & 3), A_BYTES + B_BYTES);
        load_b(n & 3, other_chunk(n - 4, j) * 256);
      };
      auto try_ahead = [&](int n) {
        if (n < 7 && !ahead && mbar_test(empty0 + 8 * (n - 3), 0)) { issue_b(n + 1); ahead = true; }
      };
#pragma unroll 1
      for (int n = 4; n < 11; n++) {
        const int k = K1 + n, st = k & 3;
        const int c = other_chunk(n - 4, j);
        if (!ahead) {
          mbar_wait(empty0 + 8 * st, ((k >> 2) & 1) ^ 1);
          issue_b(n);
        }
        ahead = false;
        if (n == 4) put(4);
        uint32_t it = 3;
        while (!(seen & 1) && !ready(c)) {
          if ((++it & 3) == 0) refresh(0);
          if (it > (1u << 22)) __trap();
          try_ahead(n);
        }
        if (n == 5) mbar_wait(bar_pub, 0);
        if (n == 6) bulk_wait_read<1>();
        if (n == 7) { bulk_wait<0>(); mbar_arrive(bar_pub + 8); TL(23); }
        TKP(3, k);
        load_a(st, base + st * A_BYTES, c * 256);
        try_ahead(n);
        if (n < 7) put(n + 1);
        sts32(kcur, k);
        seen >>= 1;
        if (n < 9) {
          if (ready(other_chunk(n - 2, j))) seen |= 2;
          else refresh(0);
        }
        if (n == 8) refresh(1);
      }
#pragma unroll 1
      for (int k = K1 + 11; k < KT - 3; k++) {
        const int st = k & 3, col = p2_col(k - K1, j);
        if (k == K1 + 11 || k == K1 + 18) wait_level(k == K1 + 11 ? 1 : 2);
        mbar_wait(empty0 + 8 * st, ((k >> 2) & 1) ^ 1);
        TKP(2, k);
        mbar_expect_tx(full0 + 8 * st, A_BYTES + B_BYTES);
        load_b(st, col);
        load_a(st, base + st * A_BYTES, col);
        sts32(kcur, k);
        if (k == K1 + 15) refresh(2);
        prefetch_ws(k);
        if (k == K1 + 20) { prefetch_map(&maps.ws_h[0]); prefetch_map(&maps.ws_h[1]); prefetch_map(&maps.out); }
      }
      const int c1 = p2_col(K2 - 3, j), c2 = p2_col(K2 - 2, j), c3 = c2 + 64;
      auto load_h = [&](int hs, int col, int h, int st) {
        tma_load5(base + OFF_B + hs * (B_BYTES / 2), &maps.ws_h[(col >> 6) & 1], ws_col(col), j * PR + h * (PR / 2), full0 + 8 * st);
      };
      mbar_wait(empty0 + 8, 0);
      TKP(2, KT - 3);
      mbar_expect_tx(full0 + 8, A_BYTES + B_BYTES);
      load_h(2, c1, 0, 1);
      load_a(1, base + A_BYTES, c1);
      load_a(1, base + OFF_B + 3 * (B_BYTES / 2), c3);
      sts32(kcur, KT - 3);
      wait_out_init(tag);
      mbar_arrive(bar_out + 8);
      mbar_wait(empty0 + 16, 0);
      TKP(2, KT - 2);
      mbar_expect_tx(full0 + 16, A_BYTES + B_BYTES);
      load_h(4, c2, 0, 2);
      load_a(2, base + 2 * A_BYTES, c2);
      load_h(5, c3, 0, 2);
      mbar_wait(empty0 + 24, 0);
      TKP(2, KT - 1);
      mbar_expect_tx(full0 + 24, B_BYTES);
      load_h(6, c1, 1, 3);
      load_h(7, c2, 1, 3);
      mbar_wait(empty0, 1);
      TL(17);
      mbar_expect_tx(full0, B_BYTES / 2);
      load_h(0, c3, 1, 0);
      asm volatile("cp.async.wait_all;" ::: "memory");
    }
  } else if (warp > 8) {
    const int t = tid - 288, w = warp - 9;
    float2* xs = (float2*)(aux + OFF_XS);
    float* red = (float*)(aux + OFF_RED);
    volatile uint32_t* misc = (volatile uint32_t*)(aux + OFF_MISC);

    const uint32_t ring = auxs + OFF_RING + (t >> 5) * 8192 + lane * 16;
    auto fetch_to = [&](uint32_t dst, const __nv_bfloat16* src, auto stepc, bool on) {
      if (on) {
#pragma unroll
        for (int k = 0; k < 4; k++) {
          if (decltype(stepc)::value == 256) cp_async16(dst + k * 512, src + k * 256);
          else cp_async16_once(dst + k * 512, src + k * decltype(stepc)::value);
        }
      }
      asm volatile("cp.async.commit_group;" ::: "memory");
    };
    auto fetch = [&](int slot, const __nv_bfloat16* src, auto stepc, bool on) { fetch_to(ring + slot * 2048, src, stepc, on); };
    const int nrow = w ? 5 : 6, lrow0 = w ? 1 + 5 * w : 0;
    const int row0 = bid * 16 + lrow0;
    const __nv_bfloat16* xrow = x + (size_t)row0 * D_ + lane * 8;
    const __nv_bfloat16* wrow = wd_rows + lrow0 * D_ + lane * 8;
    const int slot4 = (OFF_XS - OFF_RING) / 2048 - 4 * w + (w ? w - 1 : 2);
    auto pace = [&](int k) {
      uint32_t it = 0;
      while ((int)lds32(kcur) < k) {
        if (++it > (1u << 20)) __trap();
        __nanosleep(50);
      }
    };
    auto fetch_row = [&](const __nv_bfloat16* p, int i) { fetch(i < 4 ? i : slot4 + i - 4, p + i * D_, IC<256>{}, i < nrow); };
    auto load_row = [&](int i, uint32_t (&xv)[16]) {
      const uint32_t a = ring + (i < 4 ? i : slot4 + i - 4) * 2048;
#pragma unroll
      for (int k = 0; k < 4; k++) {
        const uint4 v = lds128(a + k * 512);
        xv[4 * k] = v.x; xv[4 * k + 1] = v.y; xv[4 * k + 2] = v.z; xv[4 * k + 3] = v.w;
      }
    };
    mbar_wait(full0, 0);
#pragma unroll
    for (int i = 0; i < 3; i++) fetch_row(xrow, i);
    const uint32_t tag = (ld_relaxed(&g_ctr) & ~(uint32_t)(NCTA - 1)) + NCTA;
    const uint32_t tag16 = (tag >> 7) & 0xffffu, tag5 = (tag16 & 31u) << 11;
    uint32_t xo[6][16];
    auto store_row = [&](int i) {
#pragma unroll
      for (int k = 0; k < 4; k++)
        *(uint4*)(out + (size_t)(row0 + i) * D_ + lane * 8 + k * 256) = make_uint4(xo[i][4 * k], xo[i][4 * k + 1], xo[i][4 * k + 2], xo[i][4 * k + 3]);
    };
    {
      uint4 wv4[4];
#pragma unroll
      for (int k = 0; k < 4; k++) wv4[k] = __ldg((const uint4*)(w_r + lane * 8 + k * 256));
      float sh[8];
      const int ri = nrow - 1 - (lane & 7);
      float wr[32];
      float wrsum = 0.f;
#pragma unroll
      for (int k = 0; k < 4; k++) {
        const uint32_t wv[4] = {wv4[k].x, wv4[k].y, wv4[k].z, wv4[k].w};
#pragma unroll
        for (int c = 0; c < 4; c++) {
          wr[8 * k + 2 * c] = bf_lo(wv[c]);
          wr[8 * k + 2 * c + 1] = bf_hi(wv[c]);
          wrsum += wr[8 * k + 2 * c] + wr[8 * k + 2 * c + 1];
        }
      }
      wrsum = warp_sum(wrsum);
#pragma unroll
      for (int q = 0; q < 8; q++) sh[q] = 0.f;
#pragma unroll 1
      for (int i = 0; i < nrow; i++) {
        uint32_t xv[16];
        if (i + 3 < nrow) pace(LN_K0 + i);
        fetch_row(xrow, i + 3);
        cp_wait<3>();
        load_row(i, xv);
        float s0 = 0.f, s1 = 0.f, q0 = 0.f, q1 = 0.f, r0 = 0.f, r1 = 0.f;
#pragma unroll
        for (int c = 0; c < 16; c++) {
          const float a = bf_lo(xv[c]), b = bf_hi(xv[c]);
          s0 += a;
          s1 += b;
          q0 = fmaf(a, a, q0);
          q1 = fmaf(b, b, q1);
          r0 = fmaf(a, wr[2 * c], r0);
          r1 = fmaf(b, wr[2 * c + 1], r1);
        }
        float s[4] = {s0 + s1, q0 + q1, r0 + r1, 0.f};
        xreduce<2, 16>(s, lane);
        xreduce<1, 8>(s, lane);
#pragma unroll
        for (int q = 5; q > 0; q--) sh[q] = sh[q - 1];
        sh[0] = s[0];
      }
#pragma unroll
      for (int i = 0; i < 6; i++) load_row(min(i, nrow - 1), xo[i]);
#pragma unroll
      for (int i = 0; i < 6; i++) fetch_row(wrow, i);
      xreduce<4, 4>(sh, lane);
      xreduce<2, 2>(sh, lane);
      xreduce<1, 1>(sh, lane);
      const float mean = __shfl_sync(0xffffffffu, sh[0], lane & 7) * (1.f / D_);
      float var = fmaf(-mean, mean, __shfl_sync(0xffffffffu, sh[0], 8 + (lane & 7)) * (1.f / D_));
      const float dot = __shfl_sync(0xffffffffu, sh[0], 16 + (lane & 7));
      if (__any_sync(0xffffffffu, mean * mean > 16.f * var)) {
#pragma unroll 1
        for (int i = 0; i < nrow; i++) {
          const uint32_t* xv = (const uint32_t*)(x + (size_t)(row0 + i) * D_) + lane;
          const float m = __shfl_sync(0xffffffffu, mean, nrow - 1 - i);
          float qq = 0.f;
#pragma unroll 4
          for (int c = 0; c < 16; c++) {
            const uint32_t v = __ldg(xv + 32 * c);
            const float a = bf_lo(v) - m, b = bf_hi(v) - m;
            qq = fmaf(a, a, fmaf(b, b, qq));
          }
          qq = warp_sum(qq) * (1.f / D_);
          if (ri == i) var = qq;
        }
      }
      const float mb = bf_round(mean);
      const float den = bf_round(sqrt_approx(bf_round(bf_round(var) + 1e-5f)));
      const float inv = rcp_approx(den);
      if (lane < nrow) st_rec(g_stat + row0 + ri, __float_as_uint(inv), __float_as_uint(mb) | tag16);
      const uint32_t u = pack_bf16(0.f, fmaf(-mb, wrsum, dot) * inv);
      const uint32_t key = lane < nrow ? ((u ^ (0x80000000u | (uint32_t)((int32_t)u >> 31))) & 0xffff0000u) | tag5 | (uint32_t)(S_ - 1 - row0 - ri) : 0u;
      const uint32_t k0 = __reduce_max_sync(0xffffffffu, key);
      const uint32_t k1 = __reduce_max_sync(0xffffffffu, key == k0 ? 0u : key);
      if (lane == 0) { st_rec(g_cand + bid * 3 + w, k0, k1); TL(26 + w); }
      const uint32_t mi = pack_bf16(mb, inv);
      auto out_rows = [&](int lo, int hi) {
#pragma unroll
        for (int i = lo; i < hi; i++) {
          const uint32_t mv = __shfl_sync(0xffffffffu, mi, nrow - 1 - i);
          const uint32_t mb2 = __byte_perm(mv, 0, 0x1010), inv2 = __byte_perm(mv, 0, 0x3232);
#pragma unroll
          for (int c = 0; c < 16; c++) xo[i][c] = bf2_fma(bf2_sub(xo[i][c], mb2), inv2, xo[i][c]);
          if (i < NST) store_row(i);
        }
      };
      out_rows(0, NST);
      if (t == 0) TL(16);
#pragma unroll
      for (int q = 0; q < 8; q++) sh[q] = 0.f;
#pragma unroll 1
      for (int i0 = 0; i0 < 6; i0 += 2) {
        uint32_t xv[2][16];
        cp_wait<4>();
        asm volatile("cp.async.commit_group;\ncp.async.commit_group;" ::: "memory");
        load_row(i0, xv[0]);
        load_row(min(i0 + 1, nrow - 1), xv[1]);
        float s0 = 0.f, s1 = 0.f, s2 = 0.f, s3 = 0.f;
#pragma unroll
        for (int c = 0; c < 16; c++) { s0 += bf_lo(xv[0][c]); s1 += bf_hi(xv[0][c]); s2 += bf_lo(xv[1][c]); s3 += bf_hi(xv[1][c]); }
#pragma unroll
        for (int q = 5; q > 1; q--) sh[q] = sh[q - 2];
        sh[1] = s0 + s1;
        sh[0] = s2 + s3;
      }
      xreduce<4, 4>(sh, lane);
      xreduce<2, 2>(sh, lane);
      xreduce<1, 1>(sh, lane);
      sh[0] += __shfl_xor_sync(0xffffffffu, sh[0], 8);
      sh[0] += __shfl_xor_sync(0xffffffffu, sh[0], 16);
      const float wv = -sh[0], hi = bf_hi(__float_as_uint(wv)), mid = bf_hi(__float_as_uint(wv - hi));
      if (lane < 6 && 5 - lane < nrow)
        st_rec(g_wsum + row0 + 5 - lane, __byte_perm(__float_as_uint(hi), __float_as_uint(mid), 0x7632), __byte_perm(__float_as_uint(wv - hi - mid), tag16, 0x5432));
      if (t == 0) TL(7);
      out_rows(NST, 6);
    }
    const int nblk = bid < NFFN ? (w ? (32 - NB0) / 2 : NB0) : 0, blk0 = w ? NB0 + (w - 1) * ((32 - NB0) / 2) : 0;
    if (t == 0) TL(2);
    const size_t guoff = (size_t)(rank * 512 + 16 * blk0 + (lane >> 3)) * F_ + (bid >> 1) * 64 + (lane & 7) * 8;
    const __nv_bfloat16 *pg = w_gate + guoff, *pu = w_up + guoff;
    auto fill = [&]() {
      pace(GU_KF);
      fetch(0, pg, IC<4 * F_>{}, nblk);
      fetch(1, pu, IC<4 * F_>{}, nblk);
      fetch(2, pg + 16 * F_, IC<4 * F_>{}, nblk);
      fetch(3, pu + 16 * F_, IC<4 * F_>{}, nblk);
#pragma unroll
      for (int i = NST; i < 5; i++) store_row(i);
      if (w == 0) store_row(5);
    };
    if (w == 0) {
      uint2 ws[8];
      uint32_t it = 0, bad;
      auto load_ws = [&]() {
#pragma unroll
        for (int i = 0; i < 8; i++) ws[i] = ld_rec(g_wsum + eb * 64 + (lane >> 1) + (lane & 1) * 512 + (i & 3) * 16 + (i >> 2) * 1024);
      };
      load_ws();
      if (lane == 0) misc[0] = tag;
      while (true) {
        bad = 0;
#pragma unroll
        for (int i = 0; i < 8; i++) bad |= (ws[i].y >> 16) ^ tag16;
        if (!poll_again(bad, it)) break;
        load_ws();
      }
#pragma unroll
      for (int i = 0; i < 8; i++) ((uint4*)(aux + OFF_WSUM))[32 * i + lane] = make_uint4(ws[i].x, ws[i].y & 0xffffu, 0u, 0u);
      fence_proxy_async_smem();
      __syncwarp();
      if (lane == 0) { mbar_arrive(bar_stat); TL(3); }
      fill();
    } else {
      uint4 kv[6], cs;
      uint32_t it = 0, bad;
      do {
        cs = ld_rec2(g_stat + half * 1024 + (w - 1) * 512 + j * 64 + 2 * lane);
        bad = ((cs.y ^ tag16) | (cs.w ^ tag16)) & 0xffffu ? 0xf800u : 0u;
#pragma unroll
        for (int i = 0; i < 6; i++) kv[i] = ld_rec2(g_cand + 2 * lane + 64 * i);
#pragma unroll
        for (int i = 0; i < 6; i++) bad |= (kv[i].x ^ tag5) | (kv[i].z ^ tag5);
      } while (poll_again(bad & 0xf800u, it));
      ((uint4*)(aux + OFF_STAT))[t - 32] = make_uint4(cs.x, __byte_perm(cs.y, 0, 0x3232), cs.z, __byte_perm(cs.w, 0, 0x3232));
      __syncwarp();
      if (lane == 0) mbar_arrive(bar_stat);
      uint32_t k0 = 0, k1 = 0;
#pragma unroll
      for (int i = 0; i < 6; i++) {
        const uint32_t c0 = max(kv[i].x, kv[i].z), c1 = max(min(kv[i].x, kv[i].z), max(kv[i].y, kv[i].w));
        k1 = max(max(k1, c1), min(k0, c0));
        k0 = max(k0, c0);
      }
      const uint32_t m0 = __reduce_max_sync(0xffffffffu, k0);
      const uint32_t m1 = __reduce_max_sync(0xffffffffu, k0 == m0 ? k1 : k0);
      if (t == 32) { misc[2] = m0; misc[3] = m1; }
      {
        const int r0 = S_ - 1 - (m0 & (S_ - 1)), r1 = S_ - 1 - (m1 & (S_ - 1));
        const uint32_t* pa = (const uint32_t*)(x + (size_t)r0 * D_ + rank * 512 + (w - 1) * 256) + lane;
        const uint32_t* pb = (const uint32_t*)(x + (size_t)r1 * D_ + rank * 512 + (w - 1) * 256) + lane;
        uint32_t xa[4], xb[4];
#pragma unroll
        for (int k = 0; k < 4; k++) { xa[k] = ld_relaxed(pa + 32 * k); xb[k] = ld_relaxed(pb + 32 * k); }
        uint2 sa = ld_rec(g_stat + r0), sb = ld_rec(g_stat + r1);
        fill();
        while (poll_again(((sa.y ^ tag16) | (sb.y ^ tag16)) & 0xffffu, it)) {
          sa = ld_rec(g_stat + r0);
          sb = ld_rec(g_stat + r1);
        }
        const uint32_t ma = __byte_perm(sa.y, 0, 0x3232), mb = __byte_perm(sb.y, 0, 0x3232);
        const float ia = __uint_as_float(sa.x), ib = __uint_as_float(sb.x);
#pragma unroll
        for (int k = 0; k < 4; k++) {
          const uint32_t da = bf2_sub(xa[k], ma), db = bf2_sub(xb[k], mb);
          const uint32_t na = pack_bf16(bf_lo(da) * ia, bf_hi(da) * ia), nb = pack_bf16(bf_lo(db) * ib, bf_hi(db) * ib);
          ((float4*)xs)[(w - 1) * 128 + 32 * k + lane] = make_float4(bf_lo(na), bf_lo(nb), bf_hi(na), bf_hi(nb));
        }
      }
    }
    named_bar(1, 96);
    if (t == 0) TL(4);
    if (t == 32) {
      mbar_wait(bar_ab + 16, 0);
      fence_proxy_async_smem();
      mbar_wait(bar_pub + 24, 0);
      tma_store(&maps.ab_ld, base + A_BYTES, j * 256 + 64, half * 1024 + eb * 128);
      bulk_commit();
      mbar_wait(bar_ab + 24, 0);
      mbar_arrive_cluster(bar_pub + 8, rank ^ 1);
      bulk_wait<0>();
      mbar_arrive(bar_pub);
    }
    if (t == 0) {
      auto flag = [&](int lv) {
        fence_gpu();
        st_relaxed(g_abflag + (eb * 2 + half) * 96 + lv * 32 + j, tag);
      };
      mbar_wait(bar_pub + 24, 0);
      flag(0);
      TL(9);
      mbar_wait(bar_pub, 0);
      flag(1);
      asm volatile("red.relaxed.gpu.global.add.u32 [%0], 1;" ::"l"(&g_ctr) : "memory");
      TL(19);
      mbar_wait(bar_pub + 8, 0);
      flag(2);
      TL(22);
    }
    __syncwarp();
    const int cb = bid & 15, kg = bid >> 4;
    const int ndn = w ? 9 : 10;
    const __nv_bfloat16* pd = w_down + (size_t)(kg * 448 + 16 * w + (lane >> 3)) * D_ + cb * 64 + (lane & 7) * 8;
    uint32_t sa = ring;
    uint4 v0[4], v1[4];
    float2 xv[4] = {};
    auto take = [&](uint4 (&v)[4]) {
      cp_wait<3>();
#pragma unroll
      for (int i = 0; i < 4; i++) v[i] = lds128(sa + i * 512);
    };
    auto next_down = [&](bool on) {
      fetch_to(sa, pd, IC<4 * D_>{}, on);
      pd += 48 * D_;
    };
    auto gemv16 = [&](float (&acc)[16], const uint4 (&v)[4], int h) {
      gemv8(acc, v[2 * h], xv[2 * h]);
      gemv8(acc, v[2 * h + 1], xv[2 * h + 1]);
    };
    if (nblk) {
      float ag[16], au[16];
#pragma unroll
      for (int i = 0; i < 16; i++) { ag[i] = 0.f; au[i] = 0.f; }
      const float2* xp = xs + 16 * blk0 + (lane >> 3);
      int kq = 2 * GU_K1;
      auto refill = [&](int kc, const __nv_bfloat16* p, bool gu) {
        if (kc < (kq >> 1)) pace(kq >> 1);
        kq += kq < 2 * GU_K0 ? 2 : 1;
        if (gu) fetch_to(sa, p, IC<4 * F_>{}, true);
        else next_down(true);
        sa = ring + ((sa - ring + 2048) & 8191);
      };
      take(v0);
      xv[0] = xp[0];
      xv[1] = xp[4];
      pg += 32 * F_;
      pu += 32 * F_;
      refill(0, pg, true);
#pragma unroll 1
      for (int b = 0; b < nblk; b++) {
        take(v1);
        int kc = lds32(kcur);
        xv[2] = xp[8];
        xv[3] = xp[12];
        xp += 16;
        pg += 16 * F_;
        gemv16(ag, v0, 0);
        refill(kc, pu, b + 2 < nblk);
        gemv16(ag, v0, 1);
        take(v0);
        kc = lds32(kcur);
        pu += 16 * F_;
        gemv16(au, v1, 0);
        xv[0] = xp[0];
        xv[1] = xp[4];
        refill(kc, pg, b + 3 < nblk);
        gemv16(au, v1, 1);
      }
      float s[32];
#pragma unroll
      for (int i = 0; i < 16; i++) { s[i] = ag[i]; s[16 + i] = au[i]; }
      xreduce<16, 16>(s, lane);
      xreduce<8, 8>(s, lane);
      mbar_wait(bar_pub + 8, 0);
      const uint32_t dst = mapa(auxs + OFF_GU + (rank * 3 + w) * 512 + (lane >> 4) * 256 + (lane & 3) * 64 + (lane & 8) * 4, (lane >> 2) & 1);
      const uint32_t dbar = mapa(bar_gu, (lane >> 2) & 1);
      st_async4(dst, s[0], s[1], s[2], s[3], dbar);
      st_async4(dst + 16, s[4], s[5], s[6], s[7], dbar);
      if (w == 0) {
        if (lane == 0) mbar_expect_tx(bar_gu, 6 * 512);
        mbar_wait(bar_gu, 0);
        const float2* r2 = (const float2*)(aux + OFF_GU) + lane;
        float2 g2 = r2[0], u2 = r2[32];
#pragma unroll
        for (int q = 1; q < 6; q++) {
          const float2 a = r2[64 * q], c = r2[64 * q + 32];
          g2.x += a.x; g2.y += a.y; u2.x += c.x; u2.y += c.y;
        }
        float hv[2];
#pragma unroll
        for (int tok = 0; tok < 2; tok++) {
          const float g = bf_round(tok ? g2.y : g2.x), u = bf_round(tok ? u2.y : u2.x);
          hv[tok] = bf_round(__fdividef(g, 1.f + __expf(-g))) * u;
        }
        st_rec(g_h + bid * 32 + lane, pack_bf16(hv[0], hv[1]), tag);
        if (lane == 0) TL(5);
      }
    } else {
#pragma unroll
      for (int u = 0; u < 4; u++) fetch(u, pd + u * 48 * D_, IC<4 * D_>{}, true);
      pd += 4 * 48 * D_;
      take(v0);
      next_down(true);
      sa += 2048;
      pace(H_K);
    }
    if (t == 64) prefetch_l2(out + (size_t)bid * 16 * D_, 16 * D_ * 2);
    if (t == 32) wait_out_init(tag);
    named_bar(1, 96);
    {
      uint4 hv[3];
      uint32_t it = 0;
      bool bad[3] = {true, true, w == 0};
      while (true) {
#pragma unroll
        for (int i = 0; i < 3; i++) if (bad[i]) hv[i] = ld_rec2(g_h + kg * 448 + 2 * (t + 96 * i));
#pragma unroll
        for (int i = 0; i < 3; i++) bad[i] = bad[i] && (hv[i].y != tag || hv[i].w != tag);
        if (!poll_again(bad[0] || bad[1] || bad[2], it)) break;
        __nanosleep(100);
      }
#pragma unroll
      for (int i = 0; i < 3; i++) {
        if (t + 96 * i < 224) ((float4*)xs)[t + 96 * i] = make_float4(bf_lo(hv[i].x), bf_hi(hv[i].x), bf_lo(hv[i].z), bf_hi(hv[i].z));
      }
    }
    named_bar(1, 96);
    if (t == 0) TL(10);
    {
      float ay[16];
#pragma unroll
      for (int q = 0; q < 16; q++) ay[q] = 0.f;
      const float2* hp = xs + 16 * w + (lane >> 3);
      xv[0] = hp[0];
      xv[1] = hp[4];
      auto unit = [&](const uint4 (&v)[4], uint4 (&vn)[4], int u) {
        take(vn);
        xv[2] = hp[8];
        xv[3] = hp[12];
        hp += 48;
        gemv16(ay, v, 0);
        xv[0] = hp[0];
        xv[1] = hp[4];
        next_down(u + 5 < ndn);
        sa = ring + ((sa - ring + 2048) & 8191);
        gemv16(ay, v, 1);
      };
#pragma unroll 1
      for (int u = 0; u < ndn; u += 2) {
        unit(v0, v1, u);
        if (u + 1 < ndn) unit(v1, v0, u + 1);
      }
      xreduce<8, 16>(ay, lane);
      xreduce<4, 8>(ay, lane);
      ((float4*)red)[w * 32 + (lane & 7) * 4 + (lane >> 3)] = make_float4(ay[0], ay[1], ay[2], ay[3]);
    }
    named_bar(1, 96);
    if (t < 64) {
      const float* r = red + 4 * lane + w;
      const uint32_t key = misc[2 + w];
      const uint32_t rb = (key ^ (0x80000000u | ~(uint32_t)((int32_t)key >> 31))) & 0xffff0000u;
      const float gate = bf_round(__fdividef(1.f, 1.f + __expf(-__uint_as_float(rb))));
      const uint32_t v = pack_bf16((r[0] + r[128] + r[256]) * gate, (r[2] + r[130] + r[258]) * gate);
      asm volatile("red.relaxed.gpu.global.add.noftz.bf16x2 [%0], %1;"
                   ::"l"(out + (size_t)(S_ - 1 - (key & (S_ - 1))) * D_ + cb * 64 + 2 * lane), "r"(v) : "memory");
      if (t == 0) TL(6);
    }
  } else {
    float acc[128];
    const int wg = warp >> 2, wi = warp & 3;
    const bool elect = (tid & 127) == 0;
    const uint32_t a_base = base + wg * (A_BYTES / 2);

    auto release = [&](int k) {
      if (elect) mbar_arrive(empty0 + 8 * (k & 3));
    };
    const int tw = wg ^ 1;
    auto mma_step = [&](int st, int scale_d, int flip = 0) {
      const uint64_t da = make_desc(SM0 + (wg ^ flip) * (A_BYTES / 2) + st * A_BYTES), db = make_desc(SM0 + OFF_B + st * B_BYTES);
      wgmma_fence();
      wgmma_n256(acc, da, db, scale_d);
      wgmma_n256(acc, da + 2, db + 2, 1);
      wgmma_n256(acc, da + 4, db + 4, 1);
      wgmma_commit();
      wgmma_n256(acc, da + 6, db + 6, 1);
      wgmma_commit();
    };
    auto stamp = [&](int k) {
      if (elect) TK(wg, k);
    };

    {
      const uint32_t dst = (rank << 24) + SM0 + (tid >> 3) * 128 + (((tid ^ (tid >> 3)) & 7) << 4);
      const char* pa = (const char*)x + (uint32_t)((half * 1024 + j * 64 + (tid >> 3)) * (D_ * 2) + (tid & 7) * 16 + 128);
      const uint32_t off = (eb * 64 + (tid >> 4) + (tid & 8) * 64) * (D_ * 2) + (tid & 7) * 16 + 128;
#pragma unroll
      for (int q = 0; q < 12; q++)
        cp_async16(dst + (q < 4 ? A_BYTES + q * 4096 : OFF_B + B_BYTES + (q - 4) * 4096),
                   q < 4 ? pa + ((q & 1) * 32 + (q >> 1) * 512) * (D_ * 2) : (const char*)(q < 8 ? wd_re : wd_im) + off + (q & 3) * (16 * D_ * 2));
      asm volatile("cp.async.commit_group;" ::: "memory");
    }
#pragma unroll 1
    for (int k = 0; k < K1 - 2; k++) {
      if (k < CP0) {
        cp_wait<CP0 - 1>();
        asm volatile("cp.async.commit_group;" ::: "memory");
        fence_proxy_async_smem();
        named_bar(4, 256);
        if (tid == 0) mbar_arrive(full0 + 8 * k);
        stamp(k);
      } else {
        stamp(k);
        mbar_wait(full0 + 8 * (k & 3), (k >> 2) & 1);
        TKC(k);
      }
      mma_step(k & 3, k, 1);
      wgmma_wait<2>();
      if (k) release(k - 1);
    }
    {
      uint2 st0, st1;
      auto stats = [&]() {
        mbar_wait(bar_stat, 0);
        st0 = lds64(auxs + OFF_STAT + (tw * 64 + wi * 16 + (lane >> 2)) * 8);
        st1 = lds64(auxs + OFF_STAT + (tw * 64 + wi * 16 + (lane >> 2)) * 8 + 64);
      };
      mbar_wait(full0 + 16, 1);
      if (tw) {
        wgmma_wait<0>();
        release(K1 - 3);
        mbar_wait(full0 + 24, 1);
        stats();
        named_bar(4, 256);
      }
      stamp(K1 - 2);
      mma_step(2, 1, 1);
      if (!tw) {
        wgmma_wait<2>();
        release(K1 - 3);
        mbar_wait(full0 + 24, 1);
      }
      stamp(K1 - 1);
      mma_step(3, 1, 1);
      if (!tw) stats();
      wgmma_fence();
      wgmma_n256_rs(acc, st0.y, st1.y, 0u, 0u, (uint64_t)((SM0 + OFF_AUX + OFF_WSUM) >> 4) | ((uint64_t)8 << 32));
      wgmma_commit();
      if (!tw) named_bar(4, 256);
      const int r8 = (lane & 1) * 4 + ((lane >> 1) & 3);
      const uint32_t dst = __shfl_sync(0xffffffffu, base + tw * 2 * A_BYTES + ((lane >> 4) * 8 + r8) * 128 + (((2 * wi + ((lane >> 3) & 1)) ^ r8) << 4), lane);
      if (tw) mbar_wait(full0, 0);
      wgmma_wait<3>();
      release(K1 - 2);
      wgmma_wait<1>();
      release(K1 - 1);
      if (tw) mbar_wait(empty0 + 24, 1);
      wgmma_wait<0>();
      if (elect) TL(12 + tw);
#pragma unroll
      for (int p = 0; p < 16; p++) {
        if (p < 8) {
          const float c0 = __uint_as_float(st0.x ^ (p < 4 ? 0 : 0x80000000u)), c1 = __uint_as_float(st1.x ^ (p < 4 ? 0 : 0x80000000u));
#pragma unroll
          for (int i = 16 * p; i < 16 * p + 16; i++) asm volatile("mul.f32 %0, %0, %1;" : "+f"(acc[i]) : "f"(i & 2 ? c1 : c0));
        }
        const float* v = acc + (p & 8) * 8 + (p & 3) * 16 + ((p >> 2) & 1);
        stmatrix_x4_t(dst + p * 2048, pack_bf16(v[0], v[4]), pack_bf16(v[2], v[6]), pack_bf16(v[8], v[12]), pack_bf16(v[10], v[14]));
        if (p == 7 && !tw) {
          mbar_wait(full0, 0);
          fence_proxy_async_smem();
        }
        if (p == 3 || p == 7 || p == 15) {
          __syncwarp();
          if (lane == 0 && (p == 15 || !tw)) mbar_arrive(bar_ab + (p == 3 ? 8 : p == 7 ? 0 : 16 + 8 * tw));
        }
        if (p == 13) {
          mbar_wait(bar_ab, 0);
          mbar_wait(full0 + 8, 0);
        }
      }
      if (elect) TL(29 + tw);
    }
#pragma unroll
    for (int i = 0; i < 128; i++) asm volatile("" : "=f"(acc[i]));
    stamp(K1);
    mma_step(0, 0);
    if (!tw) {
      fence_proxy_async_smem();
      named_bar(2, 128);
    } else {
      mbar_wait(bar_ab + 16, 0);
      fence_proxy_async_smem();
    }
    stamp(K1 + 1);
    mma_step(1, 1);
    wgmma_wait<2>();
    release(K1);
    mbar_wait(bar_ab + 24, 0);
    fence_proxy_async_smem();
#pragma unroll 1
    for (int k = K1 + 2; k < KT - 4; k++) {
      const bool early = k == K1 + 4;
      if (early) {
        wgmma_wait<0>();
        release(k - 1);
      }
      stamp(k);
      mbar_wait(full0 + 8 * (k & 3), (k >> 2) & 1);
      TKC(k);
      mma_step(k & 3, 1);
      wgmma_wait<2>();
      if (!early) release(k - 1);
    }
    const bool second = wg == 0;
    auto turn = [&](auto oc, uint32_t a, int hs) {
      const uint64_t da = make_desc(SM0 + wg * (A_BYTES / 2) + a), db = make_desc(SM0 + OFF_B + hs * (B_BYTES / 2));
      wgmma_fence();
#pragma unroll
      for (int q = 0; q < 4; q++) wgmma_n128<decltype(oc)::value>(acc, da + 2 * q, db + 2 * q);
      wgmma_commit();
    };
    constexpr uint32_t a3 = OFF_B + 3 * (B_BYTES / 2);
    const uint32_t o0 = ((lane >> 4) * 8 + (lane & 7)) * 128 + (((2 * wi + ((lane >> 3) & 1)) ^ (lane & 7)) << 4);
    auto send = [&](auto oc, uint32_t dst, uint32_t pitch) {
      constexpr int O = decltype(oc)::value;
#pragma unroll
      for (int h = 0; h < 2; h++) {
#pragma unroll
        for (int p = 0; p < 4; p++) {
          const float* v = acc + O + 32 * h + 8 * p;
          stmatrix_x4_t(dst + h * pitch + o0 + p * 2048, pack_bf16(v[0], v[1]), pack_bf16(v[2], v[3]), pack_bf16(v[4], v[5]), pack_bf16(v[6], v[7]));
        }
        fence_proxy_async_smem();
        named_bar(2 + wg, 128);
        if (elect) {
          tma_red_add(&maps.out, dst + h * pitch, eb * 64 + wg * 512, (j * 4 + O / 32 + h) * (PR / 4));
          if (h == 0) TL(24 + (O / 32) + second + 9);
        }
        __syncwarp();
      }
    };
    const float one = __uint_as_float(__shfl_sync(0xffffffffu, lds32(kcur) >> 8, 0) | 0x3f800000u);
    auto cut = [&](int lo) {
#pragma unroll
      for (int i = lo; i < lo + 64; i++) acc[i] *= one;
    };
    mbar_wait(full0, 1);
    wgmma_wait<0>();
    release(KT - 5);
    cut(0);
    if (second) {
      mbar_wait(full0 + 8, 1);
      mbar_wait(full0 + 16, 1);
      named_bar(4, 256);
    }
    stamp(KT - 4);
    turn(IC<0>{}, 0, 0);
    if (!second) mbar_wait(full0 + 8, 1);
    turn(IC<0>{}, A_BYTES, 2);
    if (!second) mbar_wait(full0 + 16, 1);
    turn(IC<0>{}, 2 * A_BYTES, 4);
    wgmma_wait<2>();
    release(0);
    turn(IC<0>{}, a3, 5);
    named_arrive(4 + second, 256);
    stamp(KT - 3);
    if (elect) {
      mbar_wait(bar_out + 8, 0);
      fence_proxy_async();
    }
    __syncwarp();
    mbar_wait(second ? bar_out : empty0 + 24, 0);
    wgmma_wait<2>();
    if (second) named_bar(2 + wg, 128);
    wgmma_wait<0>();
    if (elect && !second) mbar_arrive(bar_out);
    if (elect) TL(24 + second);
    send(IC<0>{}, second ? base + OFF_B + B_BYTES : base + 3 * A_BYTES, A_BYTES / 2);
    cut(64);
    mbar_wait(full0 + 24, 1);
    if (second) mbar_wait(full0, 0);
    named_bar(5 + second, 256);
    stamp(KT - 2);
    turn(IC<64>{}, 0, 1);
    turn(IC<64>{}, A_BYTES, 6);
    turn(IC<64>{}, 2 * A_BYTES, 7);
    if (!second) mbar_wait(full0, 0);
    turn(IC<64>{}, a3, 0);
    if (!second) named_arrive(6, 256);
    stamp(KT - 1);
    wgmma_wait<2>();
    named_bar(2 + wg, 128);
    wgmma_wait<0>();
    if (elect) TL(20 + second);
    send(IC<64>{}, a_base, A_BYTES);
    if (elect) {
      bulk_commit();
      bulk_wait_read<0>();
      if (second) TL(18);
    }
  }
}

typedef CUresult (*EncodeFn)(CUtensorMap*, CUtensorMapDataType, cuuint32_t, void*, const cuuint64_t*, const cuuint64_t*, const cuuint32_t*,
                             const cuuint32_t*, CUtensorMapInterleave, CUtensorMapSwizzle, CUtensorMapL2promotion, CUtensorMapFloatOOBfill);

void make_map(EncodeFn enc, CUtensorMap* m, void* ptr, uint64_t rows, uint64_t cols, uint32_t box_rows, CUtensorMapL2promotion promo,
              uint32_t box_cols = 64, CUtensorMapSwizzle sw = CU_TENSOR_MAP_SWIZZLE_128B) {
  cuuint64_t dims[2] = {cols, rows};
  cuuint64_t strides[1] = {cols * 2};
  cuuint32_t box[2] = {box_cols, box_rows};
  cuuint32_t es[2] = {1, 1};
  enc(m, CU_TENSOR_MAP_DATA_TYPE_BFLOAT16, 2, ptr, dims, strides, box, es, CU_TENSOR_MAP_INTERLEAVE_NONE, sw, promo,
      CU_TENSOR_MAP_FLOAT_OOB_FILL_NONE);
}

void make_map5(EncodeFn enc, CUtensorMap* m, void* ptr, uint64_t cols, uint32_t box_rows, uint32_t box_cols, CUtensorMapSwizzle sw) {
  cuuint64_t dims[5] = {cols, 2, 2, PG, 512 / PG};
  cuuint64_t strides[4] = {cols * 2 * 1024, cols * 2 * 512, cols * 2 * (512 / PG), cols * 2};
  cuuint32_t box[5] = {box_cols, 2, 2, PG, box_rows / (4 * PG)};
  cuuint32_t es[5] = {1, 1, 1, 1, 1};
  enc(m, CU_TENSOR_MAP_DATA_TYPE_BFLOAT16, 5, ptr, dims, strides, box, es, CU_TENSOR_MAP_INTERLEAVE_NONE, sw,
      CU_TENSOR_MAP_L2_PROMOTION_L2_128B, CU_TENSOR_MAP_FLOAT_OOB_FILL_NONE);
}

}

extern "C" void kernel_launch(void* const* d_in, const int* in_sizes, int n_in, void* d_out, int out_size) {
  (void)in_sizes; (void)n_in; (void)out_size;
  void* fn = nullptr;
  cudaDriverEntryPointQueryResult qr;
  cudaGetDriverEntryPoint("cuTensorMapEncodeTiled", &fn, cudaEnableDefault, &qr);
  EncodeFn enc = (EncodeFn)fn;
  void* ab = nullptr;
  cudaGetSymbolAddress(&ab, g_ab);
  Maps maps;
  const CUtensorMapL2promotion P256 = CU_TENSOR_MAP_L2_PROMOTION_L2_256B, P128 = CU_TENSOR_MAP_L2_PROMOTION_L2_128B;
  {
    cuuint64_t dims[3] = {D_, 512, 4}, strides[2] = {D_ * 2, D_ * 2 * 512};
    cuuint32_t box[3] = {64, 64, 2}, es[3] = {1, 1, 1};
    enc(&maps.x, CU_TENSOR_MAP_DATA_TYPE_BFLOAT16, 3, d_in[0], dims, strides, box, es, CU_TENSOR_MAP_INTERLEAVE_NONE,
        CU_TENSOR_MAP_SWIZZLE_128B, P256, CU_TENSOR_MAP_FLOAT_OOB_FILL_NONE);
  }
  for (int p = 0; p < 2; p++) {
    make_map5(enc, &maps.ws[p], d_in[1 + p], S_, 256, 64, CU_TENSOR_MAP_SWIZZLE_128B);
    make_map5(enc, &maps.ws_h[p], d_in[1 + p], S_, 128, 64, CU_TENSOR_MAP_SWIZZLE_128B);
    make_map5(enc, &maps.ws_pf[p], d_in[1 + p], S_, 32, 128, CU_TENSOR_MAP_SWIZZLE_NONE);
  }
  for (int p = 0; p < 2; p++) {
    cuuint64_t dims[3] = {D_, 2, 512}, strides[2] = {D_ * 2 * 512, D_ * 2};
    cuuint32_t box[3] = {64, 2, 64}, es[3] = {1, 1, 1};
    enc(&maps.wd[p], CU_TENSOR_MAP_DATA_TYPE_BFLOAT16, 3, d_in[3 + p], dims, strides, box, es, CU_TENSOR_MAP_INTERLEAVE_NONE,
        CU_TENSOR_MAP_SWIZZLE_128B, P256, CU_TENSOR_MAP_FLOAT_OOB_FILL_NONE);
  }
  make_map(enc, &maps.ab_ld, ab, 2 * D_, S_, 128, P128);
  make_map(enc, &maps.ab_st, ab, 2 * D_, S_, 64, P128);
  make_map5(enc, &maps.out, d_out, D_, 64, 64, CU_TENSOR_MAP_SWIZZLE_128B);
  cudaFuncSetAttribute(fused_kernel, cudaFuncAttributeMaxDynamicSharedMemorySize, SMEM_BYTES);
  fused_kernel<<<NCTA, 384, SMEM_BYTES, cudaStreamPerThread>>>(
      (const __nv_bfloat16*)d_in[0], (const __nv_bfloat16*)d_in[3], (const __nv_bfloat16*)d_in[4], (const __nv_bfloat16*)d_in[6],
      (const __nv_bfloat16*)d_in[7], (const __nv_bfloat16*)d_in[8], maps, (const __nv_bfloat16*)d_in[9], (__nv_bfloat16*)d_out);
}
```

```cpp
#include <cuda_runtime.h>
#include <cuda_bf16.h>
#include <cuda.h>
#include <stdint.h>

#define DEVI __device__ __forceinline__

namespace {

constexpr int S_ = 2048, D_ = 1024, F_ = 3584;
constexpr int STAGES = 4;
constexpr int A_BYTES = 128 * 64 * 2, B_BYTES = 256 * 64 * 2;
constexpr int K1 = 16, K2 = 32, KT = K1 + K2;
constexpr int NCTA = 128;
constexpr int NFFN = 112;
constexpr int CP0 = 2;
constexpr int NST = 3;
constexpr int PG = 4;
constexpr int PR = 64 / PG;
constexpr int NMIR = 4;
constexpr int NB0 = 8;
constexpr int LN_K0 = 4;
constexpr int GU_KF = 15;
constexpr int GU_K1 = 22;
constexpr int GU_K0 = 24;
constexpr int H_K = 30;
constexpr unsigned long long WS_MASK = 0xd80003ffc0ull;

constexpr uint32_t SM0 = 1024;
constexpr int OFF_B = STAGES * A_BYTES;
constexpr int OFF_AUX = OFF_B + STAGES * B_BYTES;
constexpr int OFF_RING = 0;
constexpr int OFF_XS = OFF_RING + 3 * 8192;
constexpr int OFF_GU = OFF_XS + 4096;
constexpr int OFF_WSUM = OFF_GU;
constexpr int OFF_STAT = OFF_XS + 8192;
constexpr int OFF_RED = OFF_STAT;
constexpr int OFF_FLAGS = OFF_STAT + 1536;
constexpr int OFF_BAR = OFF_STAT + 2048;
constexpr int OFF_MISC = OFF_BAR + 224;
constexpr int AUX_BYTES = OFF_MISC + 32;
constexpr int SMEM_BYTES = OFF_AUX + AUX_BYTES;
static_assert(SMEM_BYTES <= 232448, "smem");

template <int V> struct IC { static constexpr int value = V; };

struct Maps {
  CUtensorMap x, wd[2], ws[2], ws_h[2], ws_pf[2], ab_ld, ab_st, out;
};

__device__ __nv_bfloat16 g_ab[2 * D_ * S_];
__device__ uint2 g_stat[S_];
__device__ uint2 g_wsum[2 * D_];
__device__ uint2 g_cand[NCTA * 3];
__device__ uint2 g_h[F_];
__device__ __align__(128) uint32_t g_abflag[16 * 3 * 32];
__device__ uint32_t g_ctr;
#define TL(i) do {} while (0)
#define TK(r, k) do {} while (0)

#define TKP(r, k) TK(r, k)
#define TKC(k)
DEVI uint32_t smem_u32(const void* p) { return (uint32_t)__cvta_generic_to_shared(p); }
DEVI void mbar_init(uint32_t bar, uint32_t cnt) { asm volatile("mbarrier.init.shared::cta.b64 [%0], %1;" ::"r"(bar), "r"(cnt) : "memory"); }
DEVI void mbar_expect_tx(uint32_t bar, uint32_t bytes) { asm volatile("mbarrier.arrive.expect_tx.shared::cta.b64 _, [%0], %1;" ::"r"(bar), "r"(bytes) : "memory"); }
DEVI void mbar_arrive(uint32_t bar) { asm volatile("mbarrier.arrive.shared::cta.b64 _, [%0];" ::"r"(bar) : "memory"); }
DEVI void mbar_arrive_cluster(uint32_t bar, uint32_t cta) {
  asm volatile("{\n.reg .b32 ra;\nmapa.shared::cluster.u32 ra, %0, %1;\nmbarrier.arrive.shared::cluster.b64 _, [ra];\n}" ::"r"(bar), "r"(cta) : "memory");
}
DEVI uint32_t mapa(uint32_t a, uint32_t cta) { uint32_t r; asm("mapa.shared::cluster.u32 %0, %1, %2;" : "=r"(r) : "r"(a), "r"(cta)); return r; }
DEVI void st_async4(uint32_t dst, float a, float b, float c, float d, uint32_t bar) {
  asm volatile("st.async.shared::cluster.mbarrier::complete_tx::bytes.v4.f32 [%0], {%1, %2, %3, %4}, [%5];"
               ::"r"(dst), "f"(a), "f"(b), "f"(c), "f"(d), "r"(bar) : "memory");
}
DEVI bool mbar_try_wait(uint32_t bar, uint32_t parity) {
  uint32_t ok;
  asm volatile("{\n.reg .pred p;\nmbarrier.try_wait.parity.shared::cta.b64 p, [%1], %2;\nselp.u32 %0, 1, 0, p;\n}" : "=r"(ok) : "r"(bar), "r"(parity) : "memory");
  return ok;
}
DEVI bool mbar_test(uint32_t bar, uint32_t parity) {
  uint32_t ok;
  asm volatile("{\n.reg .pred p;\nmbarrier.test_wait.parity.shared::cta.b64 p, [%1], %2;\nselp.u32 %0, 1, 0, p;\n}" : "=r"(ok) : "r"(bar), "r"(parity) : "memory");
  return ok;
}
DEVI void mbar_wait(uint32_t bar, uint32_t parity) {
  uint32_t n = 0;
  while (!mbar_try_wait(bar, parity)) { if (++n > (1u << 20)) __trap(); }
}
DEVI void tma_load(uint32_t dst, const CUtensorMap* m, int c0, int c1, uint32_t bar) {
  asm volatile("cp.async.bulk.tensor.2d.shared::cluster.global.mbarrier::complete_tx::bytes [%0], [%1, {%3, %4}], [%2];"
               ::"r"(dst), "l"(m), "r"(bar), "r"(c0), "r"(c1) : "memory");
}
DEVI void tma_load3(uint32_t dst, const CUtensorMap* m, int c0, int c1, int c2, uint32_t bar) {
  asm volatile("cp.async.bulk.tensor.3d.shared::cluster.global.mbarrier::complete_tx::bytes [%0], [%1, {%3, %5, %4}], [%2];"
               ::"r"(dst), "l"(m), "r"(bar), "r"(c0), "r"(c2), "r"(c1) : "memory");
}
DEVI void tma_load5(uint32_t dst, const CUtensorMap* m, int c0, int c4, uint32_t bar) {
  asm volatile("cp.async.bulk.tensor.5d.shared::cluster.global.mbarrier::complete_tx::bytes [%0], [%1, {%3, %5, %5, %5, %4}], [%2];"
               ::"r"(dst), "l"(m), "r"(bar), "r"(c0), "r"(c4), "r"(0) : "memory");
}
DEVI void tma_store(const CUtensorMap* m, uint32_t src, int c0, int c1) {
  asm volatile("cp.async.bulk.tensor.2d.global.shared::cta.bulk_group [%0, {%2, %3}], [%1];" ::"l"(m), "r"(src), "r"(c0), "r"(c1) : "memory");
}
DEVI void tma_red_add(const CUtensorMap* m, uint32_t src, int c0, int c1) {
  asm volatile("cp.reduce.async.bulk.tensor.5d.global.shared::cta.add.bulk_group [%0, {%2, %4, %4, %4, %3}], [%1];" ::"l"(m), "r"(src), "r"(c0), "r"(c1), "r"(0) : "memory");
}
DEVI uint4 lds128(uint32_t a) { uint4 v; asm volatile("ld.shared.v4.u32 {%0,%1,%2,%3}, [%4];" : "=r"(v.x), "=r"(v.y), "=r"(v.z), "=r"(v.w) : "r"(a) : "memory"); return v; }
DEVI uint2 lds64(uint32_t a) { uint2 v; asm volatile("ld.shared.v2.u32 {%0,%1}, [%2];" : "=r"(v.x), "=r"(v.y) : "r"(a) : "memory"); return v; }
DEVI uint32_t lds32(uint32_t a) { uint32_t v; asm volatile("ld.volatile.shared.u32 %0, [%1];" : "=r"(v) : "r"(a) : "memory"); return v; }
DEVI void sts32(uint32_t a, uint32_t v) { asm volatile("st.volatile.shared.u32 [%0], %1;" ::"r"(a), "r"(v) : "memory"); }
DEVI void tma_prefetch(const CUtensorMap* m, int c0, int c1) {
  asm volatile("cp.async.bulk.prefetch.tensor.5d.L2.global [%0, {%1, %3, %3, %3, %2}];" ::"l"(m), "r"(c0), "r"(c1), "r"(0) : "memory");
}
DEVI void cp_async16(uint32_t dst, const void* src) { asm volatile("cp.async.cg.shared.global [%0], [%1], 16;" ::"r"(dst), "l"(src) : "memory"); }
DEVI void cp_async16_once(uint32_t dst, const void* src) {
  asm volatile("{\n.reg .b64 pol;\ncreatepolicy.fractional.L2::evict_first.b64 pol, 1.0;\n"
               "cp.async.cg.shared.global.L2::cache_hint [%0], [%1], 16, pol;\n}" ::"r"(dst), "l"(src) : "memory");
}
DEVI bool elect_one() {
  uint32_t p;
  asm volatile("{\n.reg .pred P;\nelect.sync _|P, 0xffffffff;\nselp.u32 %0, 1, 0, P;\n}" : "=r"(p));
  return p;
}
DEVI float sqrt_approx(float v) { float r; asm("sqrt.approx.ftz.f32 %0, %1;" : "=f"(r) : "f"(v)); return r; }
DEVI float rcp_approx(float v) { float r; asm("rcp.approx.ftz.f32 %0, %1;" : "=f"(r) : "f"(v)); return r; }
DEVI void bulk_commit() { asm volatile("cp.async.bulk.commit_group;" ::: "memory"); }
template <int N> DEVI void bulk_wait() { asm volatile("cp.async.bulk.wait_group %0;" ::"n"(N) : "memory"); }
template <int N> DEVI void bulk_wait_read() { asm volatile("cp.async.bulk.wait_group.read %0;" ::"n"(N) : "memory"); }
DEVI void fence_proxy_async() { asm volatile("fence.proxy.async.global;" ::: "memory"); }
DEVI void fence_proxy_async_smem() { asm volatile("fence.proxy.async.shared::cta;" ::: "memory"); }
DEVI void prefetch_map(const CUtensorMap* m) { asm volatile("prefetch.tensormap [%0];" ::"l"(m) : "memory"); }
DEVI void named_bar(int id, int n) { asm volatile("bar.sync %0, %1;" ::"r"(id), "r"(n) : "memory"); }
DEVI void named_arrive(int id, int n) { asm volatile("bar.arrive %0, %1;" ::"r"(id), "r"(n) : "memory"); }
DEVI void wgmma_fence() { asm volatile("wgmma.fence.sync.aligned;" ::: "memory"); }
DEVI void wgmma_commit() { asm volatile("wgmma.commit_group.sync.aligned;" ::: "memory"); }
template <int N> DEVI void wgmma_wait() { asm volatile("wgmma.wait_group.sync.aligned %0;" ::"n"(N) : "memory"); }
DEVI uint64_t make_desc(uint32_t addr) {
  return (uint64_t)((addr & 0x3FFFF) >> 4) | ((uint64_t)1 << 16) | ((uint64_t)64 << 32) | ((uint64_t)1 << 62);
}
DEVI uint32_t ld_acquire(const uint32_t* p) { uint32_t v; asm volatile("ld.acquire.gpu.global.u32 %0, [%1];" : "=r"(v) : "l"(p) : "memory"); return v; }
DEVI void fence_gpu() { asm volatile("fence.acq_rel.gpu;" ::: "memory"); }
DEVI uint32_t ld_relaxed(const uint32_t* p) { uint32_t v; asm volatile("ld.relaxed.gpu.global.u32 %0, [%1];" : "=r"(v) : "l"(p) : "memory"); return v; }
DEVI void st_rec(uint2* p, uint32_t a, uint32_t b) {
  asm volatile("{\n.reg .b64 t;\nmov.b64 t, {%1, %2};\nst.relaxed.gpu.global.b64 [%0], t;\n}" ::"l"(p), "r"(a), "r"(b) : "memory");
}
DEVI uint4 ld_rec2(const uint2* p) {
  uint4 v;
  asm volatile("{\n.reg .b64 a, b;\nld.relaxed.gpu.global.v2.b64 {a, b}, [%4];\nmov.b64 {%0, %1}, a;\nmov.b64 {%2, %3}, b;\n}"
               : "=r"(v.x), "=r"(v.y), "=r"(v.z), "=r"(v.w) : "l"(p) : "memory");
  return v;
}
DEVI uint2 ld_rec(const uint2* p) {
  uint2 v;
  asm volatile("{\n.reg .b64 a;\nld.relaxed.gpu.global.b64 a, [%2];\nmov.b64 {%0, %1}, a;\n}" : "=r"(v.x), "=r"(v.y) : "l"(p) : "memory");
  return v;
}
DEVI bool poll_again(bool bad, uint32_t& it) {
  if (!__any_sync(0xffffffffu, bad)) return false;
  if (++it > (1u << 18)) __trap();
  __nanosleep(40);
  return true;
}
DEVI void st_relaxed(uint32_t* p, uint32_t v) { asm volatile("st.relaxed.gpu.global.u32 [%0], %1;" ::"l"(p), "r"(v) : "memory"); }
DEVI uint32_t pack_bf16(float lo, float hi) { uint32_t r; asm("cvt.rn.bf16x2.f32 %0, %1, %2;" : "=r"(r) : "f"(hi), "f"(lo)); return r; }
DEVI float bf_lo(uint32_t v) { return __uint_as_float(v << 16); }
DEVI float bf_hi(uint32_t v) { return __uint_as_float(v & 0xffff0000u); }
DEVI float bf_round(float v) { return bf_hi(pack_bf16(0.f, v)); }
DEVI uint32_t bf2_sub(uint32_t a, uint32_t b) { uint32_t r; asm("sub.rn.bf16x2 %0, %1, %2;" : "=r"(r) : "r"(a), "r"(b)); return r; }
DEVI uint32_t bf2_fma(uint32_t a, uint32_t b, uint32_t c) { uint32_t r; asm("fma.rn.bf16x2 %0, %1, %2, %3;" : "=r"(r) : "r"(a), "r"(b), "r"(c)); return r; }
DEVI void prefetch_l2(const void* p, uint32_t bytes) { asm volatile("cp.async.bulk.prefetch.L2.global [%0], %1;" ::"l"(p), "r"(bytes) : "memory"); }
DEVI void stmatrix_x4(uint32_t addr, uint32_t a, uint32_t b, uint32_t c, uint32_t d) {
  asm volatile("stmatrix.sync.aligned.m8n8.x4.shared.b16 [%0], {%1,%2,%3,%4};" ::"r"(addr), "r"(a), "r"(b), "r"(c), "r"(d) : "memory");
}
DEVI void stmatrix_x4_t(uint32_t addr, uint32_t a, uint32_t b, uint32_t c, uint32_t d) {
  asm volatile("stmatrix.sync.aligned.m8n8.x4.trans.shared.b16 [%0], {%1,%2,%3,%4};" ::"r"(addr), "r"(a), "r"(b), "r"(c), "r"(d) : "memory");
}
DEVI void gemv8(float (&acc)[16], const uint4& v, const float2 xv) {
  const uint32_t g4[4] = {v.x, v.y, v.z, v.w};
#pragma unroll
  for (int c = 0; c < 4; c++) {
    const float lo = bf_lo(g4[c]), hi = bf_hi(g4[c]);
    acc[4 * c + 0] = fmaf(lo, xv.x, acc[4 * c + 0]);
    acc[4 * c + 1] = fmaf(lo, xv.y, acc[4 * c + 1]);
    acc[4 * c + 2] = fmaf(hi, xv.x, acc[4 * c + 2]);
    acc[4 * c + 3] = fmaf(hi, xv.y, acc[4 * c + 3]);
  }
}
template <int H, int MASK, int N> DEVI void xreduce(float (&s)[N], int lane) {
  const bool up = lane & MASK;
#pragma unroll
  for (int i = 0; i < H; i++) {
    const float keep = up ? s[i + H] : s[i], send = up ? s[i] : s[i + H];
    s[i] = keep + __shfl_xor_sync(0xffffffffu, send, MASK);
  }
}
DEVI float warp_sum(float v) {
#pragma unroll
  for (int o = 16; o; o >>= 1) v += __shfl_xor_sync(0xffffffffu, v, o);
  return v;
}

#define ACC128 \
      "{%0,%1,%2,%3,%4,%5,%6,%7,%8,%9,%10,%11,%12,%13,%14,%15,%16,%17,%18,%19,%20,%21,%22,%23,%24,%25,%26,%27,%28,%29,%30,%31," \
      "%32,%33,%34,%35,%36,%37,%38,%39,%40,%41,%42,%43,%44,%45,%46,%47,%48,%49,%50,%51,%52,%53,%54,%55,%56,%57,%58,%59,%60,%61,%62,%63," \
      "%64,%65,%66,%67,%68,%69,%70,%71,%72,%73,%74,%75,%76,%77,%78,%79,%80,%81,%82,%83,%84,%85,%86,%87,%88,%89,%90,%91,%92,%93,%94,%95," \
      "%96,%97,%98,%99,%100,%101,%102,%103,%104,%105,%106,%107,%108,%109,%110,%111,%112,%113,%114,%115,%116,%117,%118,%119,%120,%121,%122,%123,%124,%125,%126,%127},"
#define R128(d) R8(d, 0), R8(d, 8), R8(d, 16), R8(d, 24), R8(d, 32), R8(d, 40), R8(d, 48), R8(d, 56), R8(d, 64), R8(d, 72), R8(d, 80), \
                R8(d, 88), R8(d, 96), R8(d, 104), R8(d, 112), R8(d, 120)
#define R8(d, i) "+f"(d[i]), "+f"(d[i + 1]), "+f"(d[i + 2]), "+f"(d[i + 3]), "+f"(d[i + 4]), "+f"(d[i + 5]), "+f"(d[i + 6]), "+f"(d[i + 7])
DEVI void wgmma_n256(float (&d)[128], uint64_t da, uint64_t db, int scale_d) {
  asm volatile("{\n.reg .pred p;\nsetp.ne.b32 p, %130, 0;\nwgmma.mma_async.sync.aligned.m64n256k16.f32.bf16.bf16 " ACC128
               " %128, %129, p, 1, 1, 0, 0;\n}\n" : R128(d) : "l"(da), "l"(db), "r"(scale_d));
}
DEVI void wgmma_n256_rs(float (&d)[128], uint32_t a0, uint32_t a1, uint32_t a2, uint32_t a3, uint64_t db) {
  asm volatile("wgmma.mma_async.sync.aligned.m64n256k16.f32.bf16.bf16 " ACC128 " {%128, %129, %130, %131}, %132, 1, 1, 1, 0;\n"
               : R128(d) : "r"(a0), "r"(a1), "r"(a2), "r"(a3), "l"(db));
}

#define ACC64 \
      "{%0,%1,%2,%3,%4,%5,%6,%7,%8,%9,%10,%11,%12,%13,%14,%15,%16,%17,%18,%19,%20,%21,%22,%23,%24,%25,%26,%27,%28,%29,%30,%31," \
      "%32,%33,%34,%35,%36,%37,%38,%39,%40,%41,%42,%43,%44,%45,%46,%47,%48,%49,%50,%51,%52,%53,%54,%55,%56,%57,%58,%59,%60,%61,%62,%63},"
template <int O> DEVI void wgmma_n128(float (&d)[128], uint64_t da, uint64_t db) {
  asm volatile("wgmma.mma_async.sync.aligned.m64n128k16.f32.bf16.bf16 " ACC64 " %64, %65, 1, 1, 1, 0, 0;\n"
               : R8(d, O), R8(d, O + 8), R8(d, O + 16), R8(d, O + 24), R8(d, O + 32), R8(d, O + 40), R8(d, O + 48), R8(d, O + 56)
               : "l"(da), "l"(db));
}

DEVI void wait_out_init(uint32_t tag) {
  uint32_t it = 0;
  while ((int32_t)(ld_acquire(&g_ctr) - tag) < 0) { if (++it > (1u << 20)) __trap(); }
}
template <int N> DEVI void cp_wait() { asm volatile("cp.async.wait_group %0;" ::"n"(N) : "memory"); }

DEVI int other_chunk(int m, int j) { return m + (m >= j); }
DEVI int p2_col(int n, int j) {
  const int m = n < 18 ? n - 11 : (n - 18) >> 1;
  const int slab = n < 18 ? 1 : 2 + (n & 1);
  return other_chunk(m, j) * 256 + slab * 64;
}

__global__ void __cluster_dims__(2, 1, 1) __launch_bounds__(384, 1)
fused_kernel(const __nv_bfloat16* __restrict__ x, const __nv_bfloat16* __restrict__ wd_re, const __nv_bfloat16* __restrict__ wd_im,
             const __nv_bfloat16* __restrict__ w_r, const __nv_bfloat16* __restrict__ w_gate, const __nv_bfloat16* __restrict__ w_up,
             const __grid_constant__ Maps maps, const __nv_bfloat16* __restrict__ w_down, __nv_bfloat16* __restrict__ out) {
  extern __shared__ __align__(1024) uint8_t smem[];
  const uint32_t rank = blockIdx.x & 1;
  const uint32_t base = smem_u32(smem);
  uint8_t* aux = smem + OFF_AUX;
  const uint32_t auxs = base + OFF_AUX;
  const uint32_t full0 = auxs + OFF_BAR, empty0 = full0 + 8 * STAGES, bar_stat = empty0 + 8 * STAGES, bar_ab = bar_stat + 8,
                 bar_out = bar_ab + 32, bar_pub = bar_out + 64, bar_gu = bar_pub + 16;
  const uint32_t kcur = auxs + OFF_MISC + 16;

  const int tid = threadIdx.x, lane = tid & 31;
  if (tid == 256) TL(0);
  const int cl = blockIdx.x >> 1;
  const int pos = cl - 4 + max(((cl - 29) * 37) >> 8, 0) + ((cl - 4) >> 31 & (7 * cl + 36));
  const int j = (~pos & 3) * 2 + (pos >> 5), half = (pos >> 2) & 1, eb = (((pos >> 3) + (pos >> 5)) & 3) * 2 + rank;
  {
    const uint32_t dst = base + (tid >> 3) * 128 + (((tid ^ (tid >> 3)) & 7) << 4);
    const char* pa = (const char*)x + (uint32_t)((half * 1024 + j * 64 + (tid >> 3)) * (D_ * 2) + (tid & 7) * 16);
    const uint32_t off = (eb * 64 + (tid >> 4) + (tid & 8) * 64) * (D_ * 2) + (tid & 7) * 16;
    if (tid < 256) {
#pragma unroll
      for (int q = 0; q < 12; q++)
        cp_async16(dst + (q < 4 ? q * 4096 : OFF_B + (q - 4) * 4096),
                   q < 4 ? pa + ((q & 1) * 32 + (q >> 1) * 512) * (D_ * 2) : (const char*)(q < 8 ? wd_re : wd_im) + off + (q & 3) * (16 * D_ * 2));
      asm volatile("cp.async.commit_group;" ::: "memory");
    }
    if (tid == 0) TL(15);
  }
  const int warp = __shfl_sync(0xffffffffu, tid >> 5, 0);
  const int bid = j * 16 + half * 8 + eb;
  const __nv_bfloat16* wd_rows = (bid < 64 ? wd_re : wd_im) + (size_t)(bid & 63) * 16 * D_;
  if (warp == 9) ((uint4*)(aux + OFF_FLAGS))[lane] = make_uint4(0, 0, 0, 0);
  if (tid == 256) {
    prefetch_map(&maps.x);
    prefetch_map(&maps.wd[0]);
    prefetch_map(&maps.wd[1]);
    if (base != (rank << 24) + SM0) __trap();
#pragma unroll
    for (int s = 0; s < STAGES; s++) { mbar_init(full0 + 8 * s, 1); mbar_init(empty0 + 8 * s, 2); }
    mbar_init(bar_stat, 3);
#pragma unroll
    for (int s = 0; s < 4; s++) mbar_init(bar_ab + 8 * s, 4);
    mbar_init(bar_pub, 1);
    mbar_init(bar_pub + 8, 2);
    mbar_init(bar_gu, 1);
    mbar_init(bar_pub + 24, 1);
    sts32(kcur, 0);
    mbar_init(bar_out, 1);
    mbar_init(bar_out + 8, 1);
    asm volatile("fence.mbarrier_init.release.cluster;" ::: "memory");
  }
  __syncthreads();
  asm volatile("barrier.cluster.arrive.relaxed.aligned;" ::: "memory");
  asm volatile("barrier.cluster.wait.acquire.aligned;" ::: "memory");

  if (warp == 8) {
    if (elect_one()) {
      const int arow = eb * 128;
      int pf_i = 0;
      auto prefetch_ws = [&](int k) {
        if ((WS_MASK >> k) & 1) {
          const int q = pf_i < 4 ? pf_i : pf_i < 10 ? pf_i >= 7 : 2 + (pf_i & 1);
          const int c = pf_i < 4 ? j >> 1 : other_chunk(pf_i < 7 ? pf_i - 4 : pf_i < 10 ? pf_i - 7 : (pf_i - 10) >> 1, j >> 1);
          tma_prefetch(&maps.ws_pf[q & 1], half * 1024 + (q & 2) * 256 + c * 128, (j * 8 + eb) * (PR / 8));
          pf_i++;
        }
      };
      auto ws_col = [&](int col) { return half * 1024 + (col & 128) * 4 + (col >> 8) * 64; };
      auto load_b = [&](int st, int col) { tma_load5(base + OFF_B + st * B_BYTES, &maps.ws[(col >> 6) & 1], ws_col(col), j * PR, full0 + 8 * st); };
      TL(1);
#pragma unroll 1
      for (int k = CP0; k < K1 + 2; k++) {
        const int st = k & 3;
        mbar_wait(empty0 + 8 * st, ((k >> 2) & 1) ^ 1);
        TKP(2, k);
        if (k < K1) {
          mbar_expect_tx(full0 + 8 * st, A_BYTES + B_BYTES);
          tma_load3(base + st * A_BYTES, &maps.x, k * 64, j * 64, half * 2, full0 + 8 * st);
          tma_load3(base + OFF_B + st * B_BYTES, &maps.wd[0], k * 64, 0, eb * 64, full0 + 8 * st);
          tma_load3(base + OFF_B + st * B_BYTES + B_BYTES / 2, &maps.wd[1], k * 64, 0, eb * 64, full0 + 8 * st);
        } else {
          mbar_expect_tx(full0 + 8 * st, B_BYTES);
          load_b(st, j * 256 + (k - K1) * 64);
        }
        sts32(kcur, k);
        if (k == 4) { prefetch_l2(wd_rows, 16 * D_ * 2); prefetch_map(&maps.ws[0]); prefetch_map(&maps.ws[1]); prefetch_map(&maps.ws_pf[0]); prefetch_map(&maps.ws_pf[1]); prefetch_map(&maps.ab_ld); prefetch_map(&maps.ab_st); }
        prefetch_ws(k);
      }
      mbar_wait(bar_stat, 0);
      const uint32_t tag = lds32(auxs + OFF_MISC);
      uint32_t* flags = g_abflag + (eb * 2 + half) * 96;
      auto put = [&](int h) {
        tma_store(&maps.ab_st, base + h * (A_BYTES / 2), j * 256 + (h >> 1) * 64, half * 1024 + arow + (h & 1) * 64);
        bulk_commit();
      };
      auto own_b = [&](int q) {
        mbar_wait(empty0 + 8 * q, 1);
        TKP(2, K1 + q);
        sts32(kcur, K1 + q);
        mbar_expect_tx(full0 + 8 * q, B_BYTES);
        load_b(q, j * 256 + q * 64);
      };
      mbar_wait(bar_ab + 8, 0);
      fence_proxy_async_smem();
      put(0);
      mbar_wait(bar_ab, 0);
      put(1);
      TL(8);
      own_b(2);
      bulk_wait<0>();
      TL(11);
      mbar_arrive(bar_pub + 24);
      own_b(3);
      const uint32_t mirror = auxs + OFF_FLAGS;
      uint32_t mc = 0;
      auto refresh = [&](int lv) {
        cp_async16(mirror + mc + lv * 32, flags + lv * 32);
        cp_async16(mirror + mc + lv * 32 + 16, flags + lv * 32 + 4);
        mc = (mc + 128) & (NMIR * 128 - 1);
      };
      auto ready = [&](int f) {
        uint32_t v[NMIR];
#pragma unroll
        for (int i = 0; i < NMIR; i++) v[i] = lds32(mirror + f * 4 + i * 128);
        bool r = false;
#pragma unroll
        for (int i = 0; i < NMIR; i++) r |= v[i] == tag;
        return r;
      };
      auto level_set = [&](int lv) {
        bool r = false;
#pragma unroll
        for (int i = 0; i < NMIR; i++) {
          const uint4 u = lds128(mirror + i * 128 + lv * 32), v = lds128(mirror + i * 128 + lv * 32 + 16);
          r |= ((u.x ^ tag) | (u.y ^ tag) | (u.z ^ tag) | (u.w ^ tag) | (v.x ^ tag) | (v.y ^ tag) | (v.z ^ tag) | (v.w ^ tag)) == 0;
        }
        return r;
      };
      auto wait_level = [&](int lv) {
        uint32_t it = 0;
        while (!level_set(lv)) {
          refresh(lv);
          if (++it > (1u << 20)) __trap();
          __nanosleep(150);
        }
      };
      auto load_a = [&](int st, uint32_t dst, int col) { tma_load(dst, &maps.ab_ld, col, half * 1024 + arow, full0 + 8 * st); };
      mbar_wait(bar_ab + 16, 0);
      mbar_wait(bar_ab + 24, 0);
      fence_proxy_async_smem();
      refresh(0);
      {
        uint32_t it = 0;
        while (!mbar_test(empty0, 0)) {
          __nanosleep(150);
          refresh(0);
          if (++it > (1u << 20)) __trap();
        }
      }
      uint32_t seen = 0;
      bool ahead = false;
      auto issue_b = [&](int n) {
        TKP(2, K1 + n);
        mbar_expect_tx(full0 + 8 * (n & 3), A_BYTES + B_BYTES);
        load_b(n & 3, other_chunk(n - 4, j) * 256);
      };
      auto try_ahead = [&](int n) {
        if (n < 7 && !ahead && mbar_test(empty0 + 8 * (n - 3), 0)) { issue_b(n + 1); ahead = true; }
      };
#pragma unroll 1
      for (int n = 4; n < 11; n++) {
        const int k = K1 + n, st = k & 3;
        const int c = other_chunk(n - 4, j);
        if (!ahead) {
          mbar_wait(empty0 + 8 * st, ((k >> 2) & 1) ^ 1);
          issue_b(n);
        }
        ahead = false;
        if (n == 4) put(4);
        uint32_t it = 3;
        while (!(seen & 1) && !ready(c)) {
          if ((++it & 3) == 0) refresh(0);
          if (it > (1u << 22)) __trap();
          try_ahead(n);
        }
        if (n == 5) mbar_wait(bar_pub, 0);
        if (n == 6) bulk_wait_read<1>();
        if (n == 7) { bulk_wait<0>(); mbar_arrive(bar_pub + 8); TL(23); }
        TKP(3, k);
        load_a(st, base + st * A_BYTES, c * 256);
        try_ahead(n);
        if (n < 7) put(n + 1);
        sts32(kcur, k);
        seen >>= 1;
        if (n < 9) {
          if (ready(other_chunk(n - 2, j))) seen |= 2;
          else refresh(0);
        }
        if (n == 8) refresh(1);
      }
#pragma unroll 1
      for (int k = K1 + 11; k < KT - 3; k++) {
        const int st = k & 3, col = p2_col(k - K1, j);
        if (k == K1 + 11 || k == K1 + 18) wait_level(k == K1 + 11 ? 1 : 2);
        mbar_wait(empty0 + 8 * st, ((k >> 2) & 1) ^ 1);
        TKP(2, k);
        mbar_expect_tx(full0 + 8 * st, A_BYTES + B_BYTES);
        load_b(st, col);
        load_a(st, base + st * A_BYTES, col);
        sts32(kcur, k);
        if (k == K1 + 15) refresh(2);
        prefetch_ws(k);
        if (k == K1 + 20) { prefetch_map(&maps.ws_h[0]); prefetch_map(&maps.ws_h[1]); prefetch_map(&maps.out); }
      }
      const int c1 = p2_col(K2 - 3, j), c2 = p2_col(K2 - 2, j), c3 = c2 + 64;
      auto load_h = [&](int hs, int col, int h, int st) {
        tma_load5(base + OFF_B + hs * (B_BYTES / 2), &maps.ws_h[(col >> 6) & 1], ws_col(col), j * PR + h * (PR / 2), full0 + 8 * st);
      };
      mbar_wait(empty0 + 8, 0);
      TKP(2, KT - 3);
      mbar_expect_tx(full0 + 8, A_BYTES + B_BYTES);
      load_h(2, c1, 0, 1);
      load_a(1, base + A_BYTES, c1);
      load_a(1, base + OFF_B + 3 * (B_BYTES / 2), c3);
      sts32(kcur, KT - 3);
      wait_out_init(tag);
      mbar_arrive(bar_out + 8);
      mbar_wait(empty0 + 16, 0);
      TKP(2, KT - 2);
      mbar_expect_tx(full0 + 16, A_BYTES + B_BYTES);
      load_h(4, c2, 0, 2);
      load_a(2, base + 2 * A_BYTES, c2);
      load_h(5, c3, 0, 2);
      mbar_wait(empty0 + 24, 0);
      TKP(2, KT - 1);
      mbar_expect_tx(full0 + 24, B_BYTES);
      load_h(6, c1, 1, 3);
      load_h(7, c2, 1, 3);
      mbar_wait(empty0, 1);
      TL(17);
      mbar_expect_tx(full0, B_BYTES / 2);
      load_h(0, c3, 1, 0);
      asm volatile("cp.async.wait_all;" ::: "memory");
    }
  } else if (warp > 8) {
    const int t = tid - 288, w = warp - 9;
    float2* xs = (float2*)(aux + OFF_XS);
    float* red = (float*)(aux + OFF_RED);
    volatile uint32_t* misc = (volatile uint32_t*)(aux + OFF_MISC);

    const uint32_t ring = auxs + OFF_RING + (t >> 5) * 8192 + lane * 16;
    auto fetch_to = [&](uint32_t dst, const __nv_bfloat16* src, auto stepc, bool on) {
      if (on) {
#pragma unroll
        for (int k = 0; k < 4; k++) {
          if (decltype(stepc)::value == 256) cp_async16(dst + k * 512, src + k * 256);
          else cp_async16_once(dst + k * 512, src + k * decltype(stepc)::value);
        }
      }
      asm volatile("cp.async.commit_group;" ::: "memory");
    };
    auto fetch = [&](int slot, const __nv_bfloat16* src, auto stepc, bool on) { fetch_to(ring + slot * 2048, src, stepc, on); };
    const int nrow = w ? 5 : 6, lrow0 = w ? 1 + 5 * w : 0;
    const int row0 = bid * 16 + lrow0;
    const __nv_bfloat16* xrow = x + (size_t)row0 * D_ + lane * 8;
    const __nv_bfloat16* wrow = wd_rows + lrow0 * D_ + lane * 8;
    const int slot4 = (OFF_XS - OFF_RING) / 2048 - 4 * w + (w ? w - 1 : 2);
    auto pace = [&](int k) {
      uint32_t it = 0;
      while ((int)lds32(kcur) < k) {
        if (++it > (1u << 20)) __trap();
        __nanosleep(50);
      }
    };
    auto fetch_row = [&](const __nv_bfloat16* p, int i) { fetch(i < 4 ? i : slot4 + i - 4, p + i * D_, IC<256>{}, i < nrow); };
    auto load_row = [&](int i, uint32_t (&xv)[16]) {
      const uint32_t a = ring + (i < 4 ? i : slot4 + i - 4) * 2048;
#pragma unroll
      for (int k = 0; k < 4; k++) {
        const uint4 v = lds128(a + k * 512);
        xv[4 * k] = v.x; xv[4 * k + 1] = v.y; xv[4 * k + 2] = v.z; xv[4 * k + 3] = v.w;
      }
    };
    mbar_wait(full0, 0);
#pragma unroll
    for (int i = 0; i < 3; i++) fetch_row(xrow, i);
    const uint32_t tag = (ld_relaxed(&g_ctr) & ~(uint32_t)(NCTA - 1)) + NCTA;
    const uint32_t tag16 = (tag >> 7) & 0xffffu, tag5 = (tag16 & 31u) << 11;
    uint32_t xo[6][16];
    auto store_row = [&](int i) {
#pragma unroll
      for (int k = 0; k < 4; k++)
        *(uint4*)(out + (size_t)(row0 + i) * D_ + lane * 8 + k * 256) = make_uint4(xo[i][4 * k], xo[i][4 * k + 1], xo[i][4 * k + 2], xo[i][4 * k + 3]);
    };
    {
      uint4 wv4[4];
#pragma unroll
      for (int k = 0; k < 4; k++) wv4[k] = __ldg((const uint4*)(w_r + lane * 8 + k * 256));
      float sh[8];
      const int ri = nrow - 1 - (lane & 7);
      float wr[32];
      float wrsum = 0.f;
#pragma unroll
      for (int k = 0; k < 4; k++) {
        const uint32_t wv[4] = {wv4[k].x, wv4[k].y, wv4[k].z, wv4[k].w};
#pragma unroll
        for (int c = 0; c < 4; c++) {
          wr[8 * k + 2 * c] = bf_lo(wv[c]);
          wr[8 * k + 2 * c + 1] = bf_hi(wv[c]);
          wrsum += wr[8 * k + 2 * c] + wr[8 * k + 2 * c + 1];
        }
      }
      wrsum = warp_sum(wrsum);
#pragma unroll
      for (int q = 0; q < 8; q++) sh[q] = 0.f;
#pragma unroll 1
      for (int i = 0; i < nrow; i++) {
        uint32_t xv[16];
        if (i + 3 < nrow) pace(LN_K0 + i);
        fetch_row(xrow, i + 3);
        cp_wait<3>();
        load_row(i, xv);
        float s0 = 0.f, s1 = 0.f, q0 = 0.f, q1 = 0.f, r0 = 0.f, r1 = 0.f;
#pragma unroll
        for (int c = 0; c < 16; c++) {
          const float a = bf_lo(xv[c]), b = bf_hi(xv[c]);
          s0 += a;
          s1 += b;
          q0 = fmaf(a, a, q0);
          q1 = fmaf(b, b, q1);
          r0 = fmaf(a, wr[2 * c], r0);
          r1 = fmaf(b, wr[2 * c + 1], r1);
        }
        float s[4] = {s0 + s1, q0 + q1, r0 + r1, 0.f};
        xreduce<2, 16>(s, lane);
        xreduce<1, 8>(s, lane);
#pragma unroll
        for (int q = 5; q > 0; q--) sh[q] = sh[q - 1];
        sh[0] = s[0];
      }
#pragma unroll
      for (int i = 0; i < 6; i++) load_row(min(i, nrow - 1), xo[i]);
#pragma unroll
      for (int i = 0; i < 6; i++) fetch_row(wrow, i);
      xreduce<4, 4>(sh, lane);
      xreduce<2, 2>(sh, lane);
      xreduce<1, 1>(sh, lane);
      const float mean = __shfl_sync(0xffffffffu, sh[0], lane & 7) * (1.f / D_);
      float var = fmaf(-mean, mean, __shfl_sync(0xffffffffu, sh[0], 8 + (lane & 7)) * (1.f / D_));
      const float dot = __shfl_sync(0xffffffffu, sh[0], 16 + (lane & 7));
      if (__any_sync(0xffffffffu, mean * mean > 16.f * var)) {
#pragma unroll 1
        for (int i = 0; i < nrow; i++) {
          const uint32_t* xv = (const uint32_t*)(x + (size_t)(row0 + i) * D_) + lane;
          const float m = __shfl_sync(0xffffffffu, mean, nrow - 1 - i);
          float qq = 0.f;
#pragma unroll 4
          for (int c = 0; c < 16; c++) {
            const uint32_t v = __ldg(xv + 32 * c);
            const float a = bf_lo(v) - m, b = bf_hi(v) - m;
            qq = fmaf(a, a, fmaf(b, b, qq));
          }
          qq = warp_sum(qq) * (1.f / D_);
          if (ri == i) var = qq;
        }
      }
      const float mb = bf_round(mean);
      const float den = bf_round(sqrt_approx(bf_round(bf_round(var) + 1e-5f)));
      const float inv = rcp_approx(den);
      if (lane < nrow) st_rec(g_stat + row0 + ri, __float_as_uint(inv), __float_as_uint(mb) | tag16);
      const uint32_t u = pack_bf16(0.f, fmaf(-mb, wrsum, dot) * inv);
      const uint32_t key = lane < nrow ? ((u ^ (0x80000000u | (uint32_t)((int32_t)u >> 31))) & 0xffff0000u) | tag5 | (uint32_t)(S_ - 1 - row0 - ri) : 0u;
      const uint32_t k0 = __reduce_max_sync(0xffffffffu, key);
      const uint32_t k1 = __reduce_max_sync(0xffffffffu, key == k0 ? 0u : key);
      if (lane == 0) { st_rec(g_cand + bid * 3 + w, k0, k1); TL(26 + w); }
      const uint32_t mi = pack_bf16(mb, inv);
      auto out_rows = [&](int lo, int hi) {
#pragma unroll
        for (int i = lo; i < hi; i++) {
          const uint32_t mv = __shfl_sync(0xffffffffu, mi, nrow - 1 - i);
          const uint32_t mb2 = __byte_perm(mv, 0, 0x1010), inv2 = __byte_perm(mv, 0, 0x3232);
#pragma unroll
          for (int c = 0; c < 16; c++) xo[i][c] = bf2_fma(bf2_sub(xo[i][c], mb2), inv2, xo[i][c]);
          if (i < NST) store_row(i);
        }
      };
      out_rows(0, NST);
      if (t == 0) TL(16);
#pragma unroll
      for (int q = 0; q < 8; q++) sh[q] = 0.f;
#pragma unroll 1
      for (int i0 = 0; i0 < 6; i0 += 2) {
        uint32_t xv[2][16];
        cp_wait<4>();
        asm volatile("cp.async.commit_group;\ncp.async.commit_group;" ::: "memory");
        load_row(i0, xv[0]);
        load_row(min(i0 + 1, nrow - 1), xv[1]);
        float s0 = 0.f, s1 = 0.f, s2 = 0.f, s3 = 0.f;
#pragma unroll
        for (int c = 0; c < 16; c++) { s0 += bf_lo(xv[0][c]); s1 += bf_hi(xv[0][c]); s2 += bf_lo(xv[1][c]); s3 += bf_hi(xv[1][c]); }
#pragma unroll
        for (int q = 5; q > 1; q--) sh[q] = sh[q - 2];
        sh[1] = s0 + s1;
        sh[0] = s2 + s3;
      }
      xreduce<4, 4>(sh, lane);
      xreduce<2, 2>(sh, lane);
      xreduce<1, 1>(sh, lane);
      sh[0] += __shfl_xor_sync(0xffffffffu, sh[0], 8);
      sh[0] += __shfl_xor_sync(0xffffffffu, sh[0], 16);
      const float wv = -sh[0], hi = bf_hi(__float_as_uint(wv)), mid = bf_hi(__float_as_uint(wv - hi));
      if (lane < 6 && 5 - lane < nrow)
        st_rec(g_wsum + row0 + 5 - lane, __byte_perm(__float_as_uint(hi), __float_as_uint(mid), 0x7632), __byte_perm(__float_as_uint(wv - hi - mid), tag16, 0x5432));
      if (t == 0) TL(7);
      out_rows(NST, 6);
    }
    const int nblk = bid < NFFN ? (w ? (32 - NB0) / 2 : NB0) : 0, blk0 = w ? NB0 + (w - 1) * ((32 - NB0) / 2) : 0;
    if (t == 0) TL(2);
    const size_t guoff = (size_t)(rank * 512 + 16 * blk0 + (lane >> 3)) * F_ + (bid >> 1) * 64 + (lane & 7) * 8;
    const __nv_bfloat16 *pg = w_gate + guoff, *pu = w_up + guoff;
    auto fill = [&]() {
      pace(GU_KF);
      fetch(0, pg, IC<4 * F_>{}, nblk);
      fetch(1, pu, IC<4 * F_>{}, nblk);
      fetch(2, pg + 16 * F_, IC<4 * F_>{}, nblk);
      fetch(3, pu + 16 * F_, IC<4 * F_>{}, nblk);
#pragma unroll
      for (int i = NST; i < 5; i++) store_row(i);
      if (w == 0) store_row(5);
    };
    if (w == 0) {
      uint2 ws[8];
      uint32_t it = 0, bad;
      auto load_ws = [&]() {
#pragma unroll
        for (int i = 0; i < 8; i++) ws[i] = ld_rec(g_wsum + eb * 64 + (lane >> 1) + (lane & 1) * 512 + (i & 3) * 16 + (i >> 2) * 1024);
      };
      load_ws();
      if (lane == 0) misc[0] = tag;
      while (true) {
        bad = 0;
#pragma unroll
        for (int i = 0; i < 8; i++) bad |= (ws[i].y >> 16) ^ tag16;
        if (!poll_again(bad, it)) break;
        load_ws();
      }
#pragma unroll
      for (int i = 0; i < 8; i++) ((uint4*)(aux + OFF_WSUM))[32 * i + lane] = make_uint4(ws[i].x, ws[i].y & 0xffffu, 0u, 0u);
      fence_proxy_async_smem();
      __syncwarp();
      if (lane == 0) { mbar_arrive(bar_stat); TL(3); }
      fill();
    } else {
      uint4 kv[6], cs;
      uint32_t it = 0, bad;
      do {
        cs = ld_rec2(g_stat + half * 1024 + (w - 1) * 512 + j * 64 + 2 * lane);
        bad = ((cs.y ^ tag16) | (cs.w ^ tag16)) & 0xffffu ? 0xf800u : 0u;
#pragma unroll
        for (int i = 0; i < 6; i++) kv[i] = ld_rec2(g_cand + 2 * lane + 64 * i);
#pragma unroll
        for (int i = 0; i < 6; i++) bad |= (kv[i].x ^ tag5) | (kv[i].z ^ tag5);
      } while (poll_again(bad & 0xf800u, it));
      ((uint4*)(aux + OFF_STAT))[t - 32] = make_uint4(cs.x, __byte_perm(cs.y, 0, 0x3232), cs.z, __byte_perm(cs.w, 0, 0x3232));
      __syncwarp();
      if (lane == 0) mbar_arrive(bar_stat);
      uint32_t k0 = 0, k1 = 0;
#pragma unroll
      for (int i = 0; i < 6; i++) {
        const uint32_t c0 = max(kv[i].x, kv[i].z), c1 = max(min(kv[i].x, kv[i].z), max(kv[i].y, kv[i].w));
        k1 = max(max(k1, c1), min(k0, c0));
        k0 = max(k0, c0);
      }
      const uint32_t m0 = __reduce_max_sync(0xffffffffu, k0);
      const uint32_t m1 = __reduce_max_sync(0xffffffffu, k0 == m0 ? k1 : k0);
      if (t == 32) { misc[2] = m0; misc[3] = m1; }
      {
        const int r0 = S_ - 1 - (m0 & (S_ - 1)), r1 = S_ - 1 - (m1 & (S_ - 1));
        const uint32_t* pa = (const uint32_t*)(x + (size_t)r0 * D_ + rank * 512 + (w - 1) * 256) + lane;
        const uint32_t* pb = (const uint32_t*)(x + (size_t)r1 * D_ + rank * 512 + (w - 1) * 256) + lane;
        uint32_t xa[4], xb[4];
#pragma unroll
        for (int k = 0; k < 4; k++) { xa[k] = ld_relaxed(pa + 32 * k); xb[k] = ld_relaxed(pb + 32 * k); }
        uint2 sa = ld_rec(g_stat + r0), sb = ld_rec(g_stat + r1);
        fill();
        while (poll_again(((sa.y ^ tag16) | (sb.y ^ tag16)) & 0xffffu, it)) {
          sa = ld_rec(g_stat + r0);
          sb = ld_rec(g_stat + r1);
        }
        const uint32_t ma = __byte_perm(sa.y, 0, 0x3232), mb = __byte_perm(sb.y, 0, 0x3232);
        const float ia = __uint_as_float(sa.x), ib = __uint_as_float(sb.x);
#pragma unroll
        for (int k = 0; k < 4; k++) {
          const uint32_t da = bf2_sub(xa[k], ma), db = bf2_sub(xb[k], mb);
          const uint32_t na = pack_bf16(bf_lo(da) * ia, bf_hi(da) * ia), nb = pack_bf16(bf_lo(db) * ib, bf_hi(db) * ib);
          ((float4*)xs)[(w - 1) * 128 + 32 * k + lane] = make_float4(bf_lo(na), bf_lo(nb), bf_hi(na), bf_hi(nb));
        }
      }
    }
    named_bar(1, 96);
    if (t == 0) TL(4);
    if (t == 32) {
      mbar_wait(bar_ab + 16, 0);
      fence_proxy_async_smem();
      mbar_wait(bar_pub + 24, 0);
      tma_store(&maps.ab_ld, base + A_BYTES, j * 256 + 64, half * 1024 + eb * 128);
      bulk_commit();
      mbar_wait(bar_ab + 24, 0);
      mbar_arrive_cluster(bar_pub + 8, rank ^ 1);
      bulk_wait<0>();
      mbar_arrive(bar_pub);
    }
    if (t == 0) {
      auto flag = [&](int lv) {
        fence_gpu();
        st_relaxed(g_abflag + (eb * 2 + half) * 96 + lv * 32 + j, tag);
      };
      mbar_wait(bar_pub + 24, 0);
      flag(0);
      TL(9);
      mbar_wait(bar_pub, 0);
      flag(1);
      asm volatile("red.relaxed.gpu.global.add.u32 [%0], 1;" ::"l"(&g_ctr) : "memory");
      TL(19);
      mbar_wait(bar_pub + 8, 0);
      flag(2);
      TL(22);
    }
    __syncwarp();
    const int cb = bid & 15, kg = bid >> 4;
    const int ndn = w ? 9 : 10;
    const __nv_bfloat16* pd = w_down + (size_t)(kg * 448 + 16 * w + (lane >> 3)) * D_ + cb * 64 + (lane & 7) * 8;
    uint32_t sa = ring;
    uint4 v0[4], v1[4];
    float2 xv[4] = {};
    auto take = [&](uint4 (&v)[4]) {
      cp_wait<3>();
#pragma unroll
      for (int i = 0; i < 4; i++) v[i] = lds128(sa + i * 512);
    };
    auto next_down = [&](bool on) {
      fetch_to(sa, pd, IC<4 * D_>{}, on);
      pd += 48 * D_;
    };
    auto gemv16 = [&](float (&acc)[16], const uint4 (&v)[4], int h) {
      gemv8(acc, v[2 * h], xv[2 * h]);
      gemv8(acc, v[2 * h + 1], xv[2 * h + 1]);
    };
    if (nblk) {
      float ag[16], au[16];
#pragma unroll
      for (int i = 0; i < 16; i++) { ag[i] = 0.f; au[i] = 0.f; }
      const float2* xp = xs + 16 * blk0 + (lane >> 3);
      int kq = 2 * GU_K1;
      auto refill = [&](int kc, const __nv_bfloat16* p, bool gu) {
        if (kc < (kq >> 1)) pace(kq >> 1);
        kq += kq < 2 * GU_K0 ? 2 : 1;
        if (gu) fetch_to(sa, p, IC<4 * F_>{}, true);
        else next_down(true);
        sa = ring + ((sa - ring + 2048) & 8191);
      };
      take(v0);
      xv[0] = xp[0];
      xv[1] = xp[4];
      pg += 32 * F_;
      pu += 32 * F_;
      refill(0, pg, true);
#pragma unroll 1
      for (int b = 0; b < nblk; b++) {
        take(v1);
        int kc = lds32(kcur);
        xv[2] = xp[8];
        xv[3] = xp[12];
        xp += 16;
        pg += 16 * F_;
        gemv16(ag, v0, 0);
        refill(kc, pu, b + 2 < nblk);
        gemv16(ag, v0, 1);
        take(v0);
        kc = lds32(kcur);
        pu += 16 * F_;
        gemv16(au, v1, 0);
        xv[0] = xp[0];
        xv[1] = xp[4];
        refill(kc, pg, b + 3 < nblk);
        gemv16(au, v1, 1);
      }
      float s[32];
#pragma unroll
      for (int i = 0; i < 16; i++) { s[i] = ag[i]; s[16 + i] = au[i]; }
      xreduce<16, 16>(s, lane);
      xreduce<8, 8>(s, lane);
      mbar_wait(bar_pub + 8, 0);
      const uint32_t dst = mapa(auxs + OFF_GU + (rank * 3 + w) * 512 + (lane >> 4) * 256 + (lane & 3) * 64 + (lane & 8) * 4, (lane >> 2) & 1);
      const uint32_t dbar = mapa(bar_gu, (lane >> 2) & 1);
      st_async4(dst, s[0], s[1], s[2], s[3], dbar);
      st_async4(dst + 16, s[4], s[5], s[6], s[7], dbar);
      if (w == 0) {
        if (lane == 0) mbar_expect_tx(bar_gu, 6 * 512);
        mbar_wait(bar_gu, 0);
        const float2* r2 = (const float2*)(aux + OFF_GU) + lane;
        float2 g2 = r2[0], u2 = r2[32];
#pragma unroll
        for (int q = 1; q < 6; q++) {
          const float2 a = r2[64 * q], c = r2[64 * q + 32];
          g2.x += a.x; g2.y += a.y; u2.x += c.x; u2.y += c.y;
        }
        float hv[2];
#pragma unroll
        for (int tok = 0; tok < 2; tok++) {
          const float g = bf_round(tok ? g2.y : g2.x), u = bf_round(tok ? u2.y : u2.x);
          hv[tok] = bf_round(__fdividef(g, 1.f + __expf(-g))) * u;
        }
        st_rec(g_h + bid * 32 + lane, pack_bf16(hv[0], hv[1]), tag);
        if (lane == 0) TL(5);
      }
    } else {
#pragma unroll
      for (int u = 0; u < 4; u++) fetch(u, pd + u * 48 * D_, IC<4 * D_>{}, true);
      pd += 4 * 48 * D_;
      take(v0);
      next_down(true);
      sa += 2048;
      pace(H_K);
    }
    if (t == 64) prefetch_l2(out + (size_t)bid * 16 * D_, 16 * D_ * 2);
    if (t == 32) wait_out_init(tag);
    named_bar(1, 96);
    {
      uint4 hv[3];
      uint32_t it = 0;
      bool bad[3] = {true, true, w == 0};
      while (true) {
#pragma unroll
        for (int i = 0; i < 3; i++) if (bad[i]) hv[i] = ld_rec2(g_h + kg * 448 + 2 * (t + 96 * i));
#pragma unroll
        for (int i = 0; i < 3; i++) bad[i] = bad[i] && (hv[i].y != tag || hv[i].w != tag);
        if (!poll_again(bad[0] || bad[1] || bad[2], it)) break;
        __nanosleep(100);
      }
#pragma unroll
      for (int i = 0; i < 3; i++) {
        if (t + 96 * i < 224) ((float4*)xs)[t + 96 * i] = make_float4(bf_lo(hv[i].x), bf_hi(hv[i].x), bf_lo(hv[i].z), bf_hi(hv[i].z));
      }
    }
    named_bar(1, 96);
    if (t == 0) TL(10);
    {
      float ay[16];
#pragma unroll
      for (int q = 0; q < 16; q++) ay[q] = 0.f;
      const float2* hp = xs + 16 * w + (lane >> 3);
      xv[0] = hp[0];
      xv[1] = hp[4];
      auto unit = [&](const uint4 (&v)[4], uint4 (&vn)[4], int u) {
        take(vn);
        xv[2] = hp[8];
        xv[3] = hp[12];
        hp += 48;
        gemv16(ay, v, 0);
        xv[0] = hp[0];
        xv[1] = hp[4];
        next_down(u + 5 < ndn);
        sa = ring + ((sa - ring + 2048) & 8191);
        gemv16(ay, v, 1);
      };
#pragma unroll 1
      for (int u = 0; u < ndn; u += 2) {
        unit(v0, v1, u);
        if (u + 1 < ndn) unit(v1, v0, u + 1);
      }
      xreduce<8, 16>(ay, lane);
      xreduce<4, 8>(ay, lane);
      ((float4*)red)[w * 32 + (lane & 7) * 4 + (lane >> 3)] = make_float4(ay[0], ay[1], ay[2], ay[3]);
    }
    named_bar(1, 96);
    if (t < 64) {
      const float* r = red + 4 * lane + w;
      const uint32_t key = misc[2 + w];
      const uint32_t rb = (key ^ (0x80000000u | ~(uint32_t)((int32_t)key >> 31))) & 0xffff0000u;
      const float gate = bf_round(__fdividef(1.f, 1.f + __expf(-__uint_as_float(rb))));
      const uint32_t v = pack_bf16((r[0] + r[128] + r[256]) * gate, (r[2] + r[130] + r[258]) * gate);
      asm volatile("red.relaxed.gpu.global.add.noftz.bf16x2 [%0], %1;"
                   ::"l"(out + (size_t)(S_ - 1 - (key & (S_ - 1))) * D_ + cb * 64 + 2 * lane), "r"(v) : "memory");
      if (t == 0) TL(6);
    }
  } else {
    float acc[128];
    const int wg = warp >> 2, wi = warp & 3;
    const bool elect = (tid & 127) == 0;
    const uint32_t a_base = base + wg * (A_BYTES / 2);

    auto release = [&](int k) {
      if (elect) mbar_arrive(empty0 + 8 * (k & 3));
    };
    const int tw = wg ^ 1;
    auto mma_step = [&](int st, int scale_d, int flip = 0) {
      const uint64_t da = make_desc(SM0 + (wg ^ flip) * (A_BYTES / 2) + st * A_BYTES), db = make_desc(SM0 + OFF_B + st * B_BYTES);
      wgmma_fence();
      wgmma_n256(acc, da, db, scale_d);
      wgmma_n256(acc, da + 2, db + 2, 1);
      wgmma_n256(acc, da + 4, db + 4, 1);
      wgmma_commit();
      wgmma_n256(acc, da + 6, db + 6, 1);
      wgmma_commit();
    };
    auto stamp = [&](int k) {
      if (elect) TK(wg, k);
    };

    {
      const uint32_t dst = (rank << 24) + SM0 + (tid >> 3) * 128 + (((tid ^ (tid >> 3)) & 7) << 4);
      const char* pa = (const char*)x + (uint32_t)((half * 1024 + j * 64 + (tid >> 3)) * (D_ * 2) + (tid & 7) * 16 + 128);
      const uint32_t off = (eb * 64 + (tid >> 4) + (tid & 8) * 64) * (D_ * 2) + (tid & 7) * 16 + 128;
#pragma unroll
      for (int q = 0; q < 12; q++)
        cp_async16(dst + (q < 4 ? A_BYTES + q * 4096 : OFF_B + B_BYTES + (q - 4) * 4096),
                   q < 4 ? pa + ((q & 1) * 32 + (q >> 1) * 512) * (D_ * 2) : (const char*)(q < 8 ? wd_re : wd_im) + off + (q & 3) * (16 * D_ * 2));
      asm volatile("cp.async.commit_group;" ::: "memory");
    }
#pragma unroll 1
    for (int k = 0; k < K1 - 2; k++) {
      if (k < CP0) {
        cp_wait<CP0 - 1>();
        asm volatile("cp.async.commit_group;" ::: "memory");
        fence_proxy_async_smem();
        named_bar(4, 256);
        if (tid == 0) mbar_arrive(full0 + 8 * k);
        stamp(k);
      } else {
        stamp(k);
        mbar_wait(full0 + 8 * (k & 3), (k >> 2) & 1);
        TKC(k);
      }
      mma_step(k & 3, k, 1);
      wgmma_wait<2>();
      if (k) release(k - 1);
    }
    {
      uint2 st0, st1;
      auto stats = [&]() {
        mbar_wait(bar_stat, 0);
        st0 = lds64(auxs + OFF_STAT + (tw * 64 + wi * 16 + (lane >> 2)) * 8);
        st1 = lds64(auxs + OFF_STAT + (tw * 64 + wi * 16 + (lane >> 2)) * 8 + 64);
      };
      mbar_wait(full0 + 16, 1);
      if (tw) {
        wgmma_wait<0>();
        release(K1 - 3);
        mbar_wait(full0 + 24, 1);
        stats();
        named_bar(4, 256);
      }
      stamp(K1 - 2);
      mma_step(2, 1, 1);
      if (!tw) {
        wgmma_wait<2>();
        release(K1 - 3);
        mbar_wait(full0 + 24, 1);
      }
      stamp(K1 - 1);
      mma_step(3, 1, 1);
      if (!tw) stats();
      wgmma_fence();
      wgmma_n256_rs(acc, st0.y, st1.y, 0u, 0u, (uint64_t)((SM0 + OFF_AUX + OFF_WSUM) >> 4) | ((uint64_t)8 << 32));
      wgmma_commit();
      if (!tw) named_bar(4, 256);
      const int r8 = (lane & 1) * 4 + ((lane >> 1) & 3);
      const uint32_t dst = __shfl_sync(0xffffffffu, base + tw * 2 * A_BYTES + ((lane >> 4) * 8 + r8) * 128 + (((2 * wi + ((lane >> 3) & 1)) ^ r8) << 4), lane);
      if (tw) mbar_wait(full0, 0);
      wgmma_wait<3>();
      release(K1 - 2);
      wgmma_wait<1>();
      release(K1 - 1);
      if (tw) mbar_wait(empty0 + 24, 1);
      wgmma_wait<0>();
      if (elect) TL(12 + tw);
#pragma unroll
      for (int p = 0; p < 16; p++) {
        if (p < 8) {
          const float c0 = __uint_as_float(st0.x ^ (p < 4 ? 0 : 0x80000000u)), c1 = __uint_as_float(st1.x ^ (p < 4 ? 0 : 0x80000000u));
#pragma unroll
          for (int i = 16 * p; i < 16 * p + 16; i++) asm volatile("mul.f32 %0, %0, %1;" : "+f"(acc[i]) : "f"(i & 2 ? c1 : c0));
        }
        const float* v = acc + (p & 8) * 8 + (p & 3) * 16 + ((p >> 2) & 1);
        stmatrix_x4_t(dst + p * 2048, pack_bf16(v[0], v[4]), pack_bf16(v[2], v[6]), pack_bf16(v[8], v[12]), pack_bf16(v[10], v[14]));
        if (p == 7 && !tw) {
          mbar_wait(full0, 0);
          fence_proxy_async_smem();
        }
        if (p == 3 || p == 7 || p == 15) {
          __syncwarp();
          if (lane == 0 && (p == 15 || !tw)) mbar_arrive(bar_ab + (p == 3 ? 8 : p == 7 ? 0 : 16 + 8 * tw));
        }
        if (p == 13) {
          mbar_wait(bar_ab, 0);
          mbar_wait(full0 + 8, 0);
        }
      }
      if (elect) TL(29 + tw);
    }
#pragma unroll
    for (int i = 0; i < 128; i++) asm volatile("" : "=f"(acc[i]));
    stamp(K1);
    mma_step(0, 0);
    if (!tw) {
      fence_proxy_async_smem();
      named_bar(2, 128);
    } else {
      mbar_wait(bar_ab + 16, 0);
      fence_proxy_async_smem();
    }
    stamp(K1 + 1);
    mma_step(1, 1);
    wgmma_wait<2>();
    release(K1);
    mbar_wait(bar_ab + 24, 0);
    fence_proxy_async_smem();
#pragma unroll 1
    for (int k = K1 + 2; k < KT - 4; k++) {
      const bool early = k == K1 + 4;
      if (early) {
        wgmma_wait<0>();
        release(k - 1);
      }
      stamp(k);
      mbar_wait(full0 + 8 * (k & 3), (k >> 2) & 1);
      TKC(k);
      mma_step(k & 3, 1);
      wgmma_wait<2>();
      if (!early) release(k - 1);
    }
    const bool second = wg == 0;
    auto turn = [&](auto oc, uint32_t a, int hs) {
      const uint64_t da = make_desc(SM0 + wg * (A_BYTES / 2) + a), db = make_desc(SM0 + OFF_B + hs * (B_BYTES / 2));
      wgmma_fence();
#pragma unroll
      for (int q = 0; q < 4; q++) wgmma_n128<decltype(oc)::value>(acc, da + 2 * q, db + 2 * q);
      wgmma_commit();
    };
    constexpr uint32_t a3 = OFF_B + 3 * (B_BYTES / 2);
    const uint32_t o0 = ((lane >> 4) * 8 + (lane & 7)) * 128 + (((2 * wi + ((lane >> 3) & 1)) ^ (lane & 7)) << 4);
    auto send = [&](auto oc, uint32_t dst, uint32_t pitch) {
      constexpr int O = decltype(oc)::value;
#pragma unroll
      for (int h = 0; h < 2; h++) {
#pragma unroll
        for (int p = 0; p < 4; p++) {
          const float* v = acc + O + 32 * h + 8 * p;
          stmatrix_x4_t(dst + h * pitch + o0 + p * 2048, pack_bf16(v[0], v[1]), pack_bf16(v[2], v[3]), pack_bf16(v[4], v[5]), pack_bf16(v[6], v[7]));
        }
        fence_proxy_async_smem();
        named_bar(2 + wg, 128);
        if (wi == 0 && elect_one()) {
          tma_red_add(&maps.out, dst + h * pitch, eb * 64 + wg * 512, (j * 4 + O / 32 + h) * (PR / 4));
          if (h == 0) TL(24 + (O / 32) + second + 9);
          if (O && h) {
            bulk_commit();
            bulk_wait_read<0>();
            if (second) TL(18);
          }
        }
        __syncwarp();
      }
    };
    const float one = __uint_as_float(__shfl_sync(0xffffffffu, lds32(kcur) >> 8, 0) | 0x3f800000u);
    auto cut = [&](int lo) {
#pragma unroll
      for (int i = lo; i < lo + 64; i++) acc[i] *= one;
    };
    mbar_wait(full0, 1);
    wgmma_wait<0>();
    release(KT - 5);
    cut(0);
    if (second) {
      mbar_wait(full0 + 8, 1);
      mbar_wait(full0 + 16, 1);
      named_bar(4, 256);
    }
    stamp(KT - 4);
    turn(IC<0>{}, 0, 0);
    if (!second) mbar_wait(full0 + 8, 1);
    turn(IC<0>{}, A_BYTES, 2);
    if (!second) mbar_wait(full0 + 16, 1);
    turn(IC<0>{}, 2 * A_BYTES, 4);
    wgmma_wait<2>();
    release(0);
    turn(IC<0>{}, a3, 5);
    named_arrive(4 + second, 256);
    stamp(KT - 3);
    if (wi == 0) {
      mbar_wait(bar_out + 8, 0);
      fence_proxy_async();
    }
    mbar_wait(second ? bar_out : empty0 + 24, 0);
    wgmma_wait<2>();
    if (second) named_bar(2 + wg, 128);
    wgmma_wait<0>();
    if (elect && !second) mbar_arrive(bar_out);
    if (elect) TL(24 + second);
    send(IC<0>{}, second ? base + OFF_B + B_BYTES : base + 3 * A_BYTES, A_BYTES / 2);
    cut(64);
    mbar_wait(full0 + 24, 1);
    if (second) mbar_wait(full0, 0);
    named_bar(5 + second, 256);
    stamp(KT - 2);
    turn(IC<64>{}, 0, 1);
    turn(IC<64>{}, A_BYTES, 6);
    turn(IC<64>{}, 2 * A_BYTES, 7);
    if (!second) mbar_wait(full0, 0);
    turn(IC<64>{}, a3, 0);
    if (!second) named_arrive(6, 256);
    stamp(KT - 1);
    wgmma_wait<2>();
    named_bar(2 + wg, 128);
    wgmma_wait<0>();
    if (elect) TL(20 + second);
    send(IC<64>{}, a_base, A_BYTES);
  }
}

typedef CUresult (*EncodeFn)(CUtensorMap*, CUtensorMapDataType, cuuint32_t, void*, const cuuint64_t*, const cuuint64_t*, const cuuint32_t*,
                             const cuuint32_t*, CUtensorMapInterleave, CUtensorMapSwizzle, CUtensorMapL2promotion, CUtensorMapFloatOOBfill);

void make_map(EncodeFn enc, CUtensorMap* m, void* ptr, uint64_t rows, uint64_t cols, uint32_t box_rows, CUtensorMapL2promotion promo,
              uint32_t box_cols = 64, CUtensorMapSwizzle sw = CU_TENSOR_MAP_SWIZZLE_128B) {
  cuuint64_t dims[2] = {cols, rows};
  cuuint64_t strides[1] = {cols * 2};
  cuuint32_t box[2] = {box_cols, box_rows};
  cuuint32_t es[2] = {1, 1};
  enc(m, CU_TENSOR_MAP_DATA_TYPE_BFLOAT16, 2, ptr, dims, strides, box, es, CU_TENSOR_MAP_INTERLEAVE_NONE, sw, promo,
      CU_TENSOR_MAP_FLOAT_OOB_FILL_NONE);
}

void make_map5(EncodeFn enc, CUtensorMap* m, void* ptr, uint64_t cols, uint32_t box_rows, uint32_t box_cols, CUtensorMapSwizzle sw) {
  cuuint64_t dims[5] = {cols, 2, 2, PG, 512 / PG};
  cuuint64_t strides[4] = {cols * 2 * 1024, cols * 2 * 512, cols * 2 * (512 / PG), cols * 2};
  cuuint32_t box[5] = {box_cols, 2, 2, PG, box_rows / (4 * PG)};
  cuuint32_t es[5] = {1, 1, 1, 1, 1};
  enc(m, CU_TENSOR_MAP_DATA_TYPE_BFLOAT16, 5, ptr, dims, strides, box, es, CU_TENSOR_MAP_INTERLEAVE_NONE, sw,
      CU_TENSOR_MAP_L2_PROMOTION_L2_128B, CU_TENSOR_MAP_FLOAT_OOB_FILL_NONE);
}

}

extern "C" void kernel_launch(void* const* d_in, const int* in_sizes, int n_in, void* d_out, int out_size) {
  (void)in_sizes; (void)n_in; (void)out_size;
  void* fn = nullptr;
  cudaDriverEntryPointQueryResult qr;
  cudaGetDriverEntryPoint("cuTensorMapEncodeTiled", &fn, cudaEnableDefault, &qr);
  EncodeFn enc = (EncodeFn)fn;
  void* ab = nullptr;
  cudaGetSymbolAddress(&ab, g_ab);
  Maps maps;
  const CUtensorMapL2promotion P256 = CU_TENSOR_MAP_L2_PROMOTION_L2_256B, P128 = CU_TENSOR_MAP_L2_PROMOTION_L2_128B;
  {
    cuuint64_t dims[3] = {D_, 512, 4}, strides[2] = {D_ * 2, D_ * 2 * 512};
    cuuint32_t box[3] = {64, 64, 2}, es[3] = {1, 1, 1};
    enc(&maps.x, CU_TENSOR_MAP_DATA_TYPE_BFLOAT16, 3, d_in[0], dims, strides, box, es, CU_TENSOR_MAP_INTERLEAVE_NONE,
        CU_TENSOR_MAP_SWIZZLE_128B, P256, CU_TENSOR_MAP_FLOAT_OOB_FILL_NONE);
  }
  for (int p = 0; p < 2; p++) {
    make_map5(enc, &maps.ws[p], d_in[1 + p], S_, 256, 64, CU_TENSOR_MAP_SWIZZLE_128B);
    make_map5(enc, &maps.ws_h[p], d_in[1 + p], S_, 128, 64, CU_TENSOR_MAP_SWIZZLE_128B);
    make_map5(enc, &maps.ws_pf[p], d_in[1 + p], S_, 32, 128, CU_TENSOR_MAP_SWIZZLE_NONE);
  }
  for (int p = 0; p < 2; p++) {
    cuuint64_t dims[3] = {D_, 2, 512}, strides[2] = {D_ * 2 * 512, D_ * 2};
    cuuint32_t box[3] = {64, 2, 64}, es[3] = {1, 1, 1};
    enc(&maps.wd[p], CU_TENSOR_MAP_DATA_TYPE_BFLOAT16, 3, d_in[3 + p], dims, strides, box, es, CU_TENSOR_MAP_INTERLEAVE_NONE,
        CU_TENSOR_MAP_SWIZZLE_128B, P256, CU_TENSOR_MAP_FLOAT_OOB_FILL_NONE);
  }
  make_map(enc, &maps.ab_ld, ab, 2 * D_, S_, 128, P128);
  make_map(enc, &maps.ab_st, ab, 2 * D_, S_, 64, P128);
  make_map5(enc, &maps.out, d_out, D_, 64, 64, CU_TENSOR_MAP_SWIZZLE_128B);
  cudaFuncSetAttribute(fused_kernel, cudaFuncAttributeMaxDynamicSharedMemorySize, SMEM_BYTES);
  fused_kernel<<<NCTA, 384, SMEM_BYTES, cudaStreamPerThread>>>(
      (const __nv_bfloat16*)d_in[0], (const __nv_bfloat16*)d_in[3], (const __nv_bfloat16*)d_in[4], (const __nv_bfloat16*)d_in[6],
      (const __nv_bfloat16*)d_in[7], (const __nv_bfloat16*)d_in[8], maps, (const __nv_bfloat16*)d_in[9], (__nv_bfloat16*)d_out);
}
```

```cpp
#include <cuda_runtime.h>
#include <cuda_bf16.h>
#include <cuda.h>
#include <stdint.h>

#define DEVI __device__ __forceinline__

namespace {

constexpr int S_ = 2048, D_ = 1024, F_ = 3584;
constexpr int STAGES = 4;
constexpr int A_BYTES = 128 * 64 * 2, B_BYTES = 256 * 64 * 2;
constexpr int K1 = 16, K2 = 32, KT = K1 + K2;
constexpr int NCTA = 128;
constexpr int NFFN = 112;
constexpr int CP0 = 2;
constexpr int NST = 3;
constexpr int PG = 4;
constexpr int PR = 64 / PG;
constexpr int NMIR = 4;
constexpr int NB0 = 8;
constexpr int LN_K0 = 4;
constexpr int GU_KF = 15;
constexpr int GU_K1 = 22;
constexpr int GU_K0 = 24;
constexpr int H_K = 30;
constexpr unsigned long long WS_MASK = 0xd80003ffc0ull;

constexpr uint32_t SM0 = 1024;
constexpr int OFF_B = STAGES * A_BYTES;
constexpr int OFF_AUX = OFF_B + STAGES * B_BYTES;
constexpr int OFF_RING = 0;
constexpr int OFF_XS = OFF_RING + 3 * 8192;
constexpr int OFF_GU = OFF_XS + 4096;
constexpr int OFF_WSUM = OFF_GU;
constexpr int OFF_STAT = OFF_XS + 8192;
constexpr int OFF_RED = OFF_STAT;
constexpr int OFF_FLAGS = OFF_STAT + 1536;
constexpr int OFF_BAR = OFF_STAT + 2048;
constexpr int OFF_MISC = OFF_BAR + 224;
constexpr int AUX_BYTES = OFF_MISC + 32;
constexpr int SMEM_BYTES = OFF_AUX + AUX_BYTES;
static_assert(SMEM_BYTES <= 232448, "smem");

template <int V> struct IC { static constexpr int value = V; };

struct Maps {
  CUtensorMap x, wd[2], ws[2], ws_h[2], ws_pf[2], ab_ld, ab_st, out;
};

__device__ __nv_bfloat16 g_ab[2 * D_ * S_];
__device__ uint2 g_stat[S_];
__device__ uint2 g_wsum[2 * D_];
__device__ uint2 g_cand[NCTA * 3];
__device__ uint2 g_h[F_];
__device__ __align__(128) uint32_t g_abflag[16 * 3 * 32];
__device__ uint32_t g_ctr;
#define TL(i) do {} while (0)
#define TK(r, k) do {} while (0)

#define TKP(r, k) TK(r, k)
#define TKC(k)
DEVI uint32_t smem_u32(const void* p) { return (uint32_t)__cvta_generic_to_shared(p); }
DEVI void mbar_init(uint32_t bar, uint32_t cnt) { asm volatile("mbarrier.init.shared::cta.b64 [%0], %1;" ::"r"(bar), "r"(cnt) : "memory"); }
DEVI void mbar_expect_tx(uint32_t bar, uint32_t bytes) { asm volatile("mbarrier.arrive.expect_tx.shared::cta.b64 _, [%0], %1;" ::"r"(bar), "r"(bytes) : "memory"); }
DEVI void mbar_arrive(uint32_t bar) { asm volatile("mbarrier.arrive.shared::cta.b64 _, [%0];" ::"r"(bar) : "memory"); }
DEVI void mbar_arrive_cluster(uint32_t bar, uint32_t cta) {
  asm volatile("{\n.reg .b32 ra;\nmapa.shared::cluster.u32 ra, %0, %1;\nmbarrier.arrive.shared::cluster.b64 _, [ra];\n}" ::"r"(bar), "r"(cta) : "memory");
}
DEVI uint32_t mapa(uint32_t a, uint32_t cta) { uint32_t r; asm("mapa.shared::cluster.u32 %0, %1, %2;" : "=r"(r) : "r"(a), "r"(cta)); return r; }
DEVI void st_async4(uint32_t dst, float a, float b, float c, float d, uint32_t bar) {
  asm volatile("st.async.shared::cluster.mbarrier::complete_tx::bytes.v4.f32 [%0], {%1, %2, %3, %4}, [%5];"
               ::"r"(dst), "f"(a), "f"(b), "f"(c), "f"(d), "r"(bar) : "memory");
}
DEVI bool mbar_try_wait(uint32_t bar, uint32_t parity) {
  uint32_t ok;
  asm volatile("{\n.reg .pred p;\nmbarrier.try_wait.parity.shared::cta.b64 p, [%1], %2;\nselp.u32 %0, 1, 0, p;\n}" : "=r"(ok) : "r"(bar), "r"(parity) : "memory");
  return ok;
}
DEVI bool mbar_test(uint32_t bar, uint32_t parity) {
  uint32_t ok;
  asm volatile("{\n.reg .pred p;\nmbarrier.test_wait.parity.shared::cta.b64 p, [%1], %2;\nselp.u32 %0, 1, 0, p;\n}" : "=r"(ok) : "r"(bar), "r"(parity) : "memory");
  return ok;
}
DEVI void mbar_wait(uint32_t bar, uint32_t parity) {
  uint32_t n = 0;
  while (!mbar_try_wait(bar, parity)) { if (++n > (1u << 20)) __trap(); }
}
DEVI void tma_load(uint32_t dst, const CUtensorMap* m, int c0, int c1, uint32_t bar) {
  asm volatile("cp.async.bulk.tensor.2d.shared::cluster.global.mbarrier::complete_tx::bytes [%0], [%1, {%3, %4}], [%2];"
               ::"r"(dst), "l"(m), "r"(bar), "r"(c0), "r"(c1) : "memory");
}
DEVI void tma_load3(uint32_t dst, const CUtensorMap* m, int c0, int c1, int c2, uint32_t bar) {
  asm volatile("cp.async.bulk.tensor.3d.shared::cluster.global.mbarrier::complete_tx::bytes [%0], [%1, {%3, %5, %4}], [%2];"
               ::"r"(dst), "l"(m), "r"(bar), "r"(c0), "r"(c2), "r"(c1) : "memory");
}
DEVI void tma_load5(uint32_t dst, const CUtensorMap* m, int c0, int c4, uint32_t bar) {
  asm volatile("{\n.reg .b64 pol;\ncreatepolicy.fractional.L2::evict_first.b64 pol, 1.0;\n"
               "cp.async.bulk.tensor.5d.shared::cluster.global.mbarrier::complete_tx::bytes.L2::cache_hint [%0], [%1, {%3, %5, %5, %5, %4}], [%2], pol;\n}"
               ::"r"(dst), "l"(m), "r"(bar), "r"(c0), "r"(c4), "r"(0) : "memory");
}
DEVI void tma_store(const CUtensorMap* m, uint32_t src, int c0, int c1) {
  asm volatile("cp.async.bulk.tensor.2d.global.shared::cta.bulk_group [%0, {%2, %3}], [%1];" ::"l"(m), "r"(src), "r"(c0), "r"(c1) : "memory");
}
DEVI void tma_red_add(const CUtensorMap* m, uint32_t src, int c0, int c1) {
  asm volatile("cp.reduce.async.bulk.tensor.5d.global.shared::cta.add.bulk_group [%0, {%2, %4, %4, %4, %3}], [%1];" ::"l"(m), "r"(src), "r"(c0), "r"(c1), "r"(0) : "memory");
}
DEVI uint4 lds128(uint32_t a) { uint4 v; asm volatile("ld.shared.v4.u32 {%0,%1,%2,%3}, [%4];" : "=r"(v.x), "=r"(v.y), "=r"(v.z), "=r"(v.w) : "r"(a) : "memory"); return v; }
DEVI uint2 lds64(uint32_t a) { uint2 v; asm volatile("ld.shared.v2.u32 {%0,%1}, [%2];" : "=r"(v.x), "=r"(v.y) : "r"(a) : "memory"); return v; }
DEVI uint32_t lds32(uint32_t a) { uint32_t v; asm volatile("ld.volatile.shared.u32 %0, [%1];" : "=r"(v) : "r"(a) : "memory"); return v; }
DEVI void sts32(uint32_t a, uint32_t v) { asm volatile("st.volatile.shared.u32 [%0], %1;" ::"r"(a), "r"(v) : "memory"); }
DEVI void tma_prefetch(const CUtensorMap* m, int c0, int c1) {
  asm volatile("cp.async.bulk.prefetch.tensor.5d.L2.global [%0, {%1, %3, %3, %3, %2}];" ::"l"(m), "r"(c0), "r"(c1), "r"(0) : "memory");
}
DEVI void cp_async16(uint32_t dst, const void* src) { asm volatile("cp.async.cg.shared.global [%0], [%1], 16;" ::"r"(dst), "l"(src) : "memory"); }
DEVI void cp_async16_once(uint32_t dst, const void* src) {
  asm volatile("{\n.reg .b64 pol;\ncreatepolicy.fractional.L2::evict_first.b64 pol, 1.0;\n"
               "cp.async.cg.shared.global.L2::cache_hint [%0], [%1], 16, pol;\n}" ::"r"(dst), "l"(src) : "memory");
}
DEVI bool elect_one() {
  uint32_t p;
  asm volatile("{\n.reg .pred P;\nelect.sync _|P, 0xffffffff;\nselp.u32 %0, 1, 0, P;\n}" : "=r"(p));
  return p;
}
DEVI float sqrt_approx(float v) { float r; asm("sqrt.approx.ftz.f32 %0, %1;" : "=f"(r) : "f"(v)); return r; }
DEVI float rcp_approx(float v) { float r; asm("rcp.approx.ftz.f32 %0, %1;" : "=f"(r) : "f"(v)); return r; }
DEVI void bulk_commit() { asm volatile("cp.async.bulk.commit_group;" ::: "memory"); }
template <int N> DEVI void bulk_wait() { asm volatile("cp.async.bulk.wait_group %0;" ::"n"(N) : "memory"); }
template <int N> DEVI void bulk_wait_read() { asm volatile("cp.async.bulk.wait_group.read %0;" ::"n"(N) : "memory"); }
DEVI void fence_proxy_async() { asm volatile("fence.proxy.async.global;" ::: "memory"); }
DEVI void fence_proxy_async_smem() { asm volatile("fence.proxy.async.shared::cta;" ::: "memory"); }
DEVI void prefetch_map(const CUtensorMap* m) { asm volatile("prefetch.tensormap [%0];" ::"l"(m) : "memory"); }
DEVI void named_bar(int id, int n) { asm volatile("bar.sync %0, %1;" ::"r"(id), "r"(n) : "memory"); }
DEVI void named_arrive(int id, int n) { asm volatile("bar.arrive %0, %1;" ::"r"(id), "r"(n) : "memory"); }
DEVI void wgmma_fence() { asm volatile("wgmma.fence.sync.aligned;" ::: "memory"); }
DEVI void wgmma_commit() { asm volatile("wgmma.commit_group.sync.aligned;" ::: "memory"); }
template <int N> DEVI void wgmma_wait() { asm volatile("wgmma.wait_group.sync.aligned %0;" ::"n"(N) : "memory"); }
DEVI uint64_t make_desc(uint32_t addr) {
  return (uint64_t)((addr & 0x3FFFF) >> 4) | ((uint64_t)1 << 16) | ((uint64_t)64 << 32) | ((uint64_t)1 << 62);
}
DEVI uint32_t ld_acquire(const uint32_t* p) { uint32_t v; asm volatile("ld.acquire.gpu.global.u32 %0, [%1];" : "=r"(v) : "l"(p) : "memory"); return v; }
DEVI void fence_gpu() { asm volatile("fence.acq_rel.gpu;" ::: "memory"); }
DEVI uint32_t ld_relaxed(const uint32_t* p) { uint32_t v; asm volatile("ld.relaxed.gpu.global.u32 %0, [%1];" : "=r"(v) : "l"(p) : "memory"); return v; }
DEVI void st_rec(uint2* p, uint32_t a, uint32_t b) {
  asm volatile("{\n.reg .b64 t;\nmov.b64 t, {%1, %2};\nst.relaxed.gpu.global.b64 [%0], t;\n}" ::"l"(p), "r"(a), "r"(b) : "memory");
}
DEVI uint4 ld_rec2(const uint2* p) {
  uint4 v;
  asm volatile("{\n.reg .b64 a, b;\nld.relaxed.gpu.global.v2.b64 {a, b}, [%4];\nmov.b64 {%0, %1}, a;\nmov.b64 {%2, %3}, b;\n}"
               : "=r"(v.x), "=r"(v.y), "=r"(v.z), "=r"(v.w) : "l"(p) : "memory");
  return v;
}
DEVI uint2 ld_rec(const uint2* p) {
  uint2 v;
  asm volatile("{\n.reg .b64 a;\nld.relaxed.gpu.global.b64 a, [%2];\nmov.b64 {%0, %1}, a;\n}" : "=r"(v.x), "=r"(v.y) : "l"(p) : "memory");
  return v;
}
DEVI bool poll_again(bool bad, uint32_t& it) {
  if (!__any_sync(0xffffffffu, bad)) return false;
  if (++it > (1u << 18)) __trap();
  __nanosleep(40);
  return true;
}
DEVI void st_relaxed(uint32_t* p, uint32_t v) { asm volatile("st.relaxed.gpu.global.u32 [%0], %1;" ::"l"(p), "r"(v) : "memory"); }
DEVI uint32_t pack_bf16(float lo, float hi) { uint32_t r; asm("cvt.rn.bf16x2.f32 %0, %1, %2;" : "=r"(r) : "f"(hi), "f"(lo)); return r; }
DEVI float bf_lo(uint32_t v) { return __uint_as_float(v << 16); }
DEVI float bf_hi(uint32_t v) { return __uint_as_float(v & 0xffff0000u); }
DEVI float bf_round(float v) { return bf_hi(pack_bf16(0.f, v)); }
DEVI uint32_t bf2_sub(uint32_t a, uint32_t b) { uint32_t r; asm("sub.rn.bf16x2 %0, %1, %2;" : "=r"(r) : "r"(a), "r"(b)); return r; }
DEVI uint32_t bf2_fma(uint32_t a, uint32_t b, uint32_t c) { uint32_t r; asm("fma.rn.bf16x2 %0, %1, %2, %3;" : "=r"(r) : "r"(a), "r"(b), "r"(c)); return r; }
DEVI void prefetch_l2(const void* p, uint32_t bytes) { asm volatile("cp.async.bulk.prefetch.L2.global [%0], %1;" ::"l"(p), "r"(bytes) : "memory"); }
DEVI void stmatrix_x4_t(uint32_t addr, uint32_t a, uint32_t b, uint32_t c, uint32_t d) {
  asm volatile("stmatrix.sync.aligned.m8n8.x4.trans.shared.b16 [%0], {%1,%2,%3,%4};" ::"r"(addr), "r"(a), "r"(b), "r"(c), "r"(d) : "memory");
}
DEVI void gemv8(float (&acc)[16], const uint4& v, const float2 xv) {
  const uint32_t g4[4] = {v.x, v.y, v.z, v.w};
#pragma unroll
  for (int c = 0; c < 4; c++) {
    const float lo = bf_lo(g4[c]), hi = bf_hi(g4[c]);
    acc[4 * c + 0] = fmaf(lo, xv.x, acc[4 * c + 0]);
    acc[4 * c + 1] = fmaf(lo, xv.y, acc[4 * c + 1]);
    acc[4 * c + 2] = fmaf(hi, xv.x, acc[4 * c + 2]);
    acc[4 * c + 3] = fmaf(hi, xv.y, acc[4 * c + 3]);
  }
}
template <int H, int MASK, int N> DEVI void xreduce(float (&s)[N], int lane) {
  const bool up = lane & MASK;
#pragma unroll
  for (int i = 0; i < H; i++) {
    const float keep = up ? s[i + H] : s[i], send = up ? s[i] : s[i + H];
    s[i] = keep + __shfl_xor_sync(0xffffffffu, send, MASK);
  }
}
DEVI float warp_sum(float v) {
#pragma unroll
  for (int o = 16; o; o >>= 1) v += __shfl_xor_sync(0xffffffffu, v, o);
  return v;
}

#define ACC128 \
      "{%0,%1,%2,%3,%4,%5,%6,%7,%8,%9,%10,%11,%12,%13,%14,%15,%16,%17,%18,%19,%20,%21,%22,%23,%24,%25,%26,%27,%28,%29,%30,%31," \
      "%32,%33,%34,%35,%36,%37,%38,%39,%40,%41,%42,%43,%44,%45,%46,%47,%48,%49,%50,%51,%52,%53,%54,%55,%56,%57,%58,%59,%60,%61,%62,%63," \
      "%64,%65,%66,%67,%68,%69,%70,%71,%72,%73,%74,%75,%76,%77,%78,%79,%80,%81,%82,%83,%84,%85,%86,%87,%88,%89,%90,%91,%92,%93,%94,%95," \
      "%96,%97,%98,%99,%100,%101,%102,%103,%104,%105,%106,%107,%108,%109,%110,%111,%112,%113,%114,%115,%116,%117,%118,%119,%120,%121,%122,%123,%124,%125,%126,%127},"
#define R128(d) R8(d, 0), R8(d, 8), R8(d, 16), R8(d, 24), R8(d, 32), R8(d, 40), R8(d, 48), R8(d, 56), R8(d, 64), R8(d, 72), R8(d, 80), \
                R8(d, 88), R8(d, 96), R8(d, 104), R8(d, 112), R8(d, 120)
#define R8(d, i) "+f"(d[i]), "+f"(d[i + 1]), "+f"(d[i + 2]), "+f"(d[i + 3]), "+f"(d[i + 4]), "+f"(d[i + 5]), "+f"(d[i + 6]), "+f"(d[i + 7])
DEVI void wgmma_n256(float (&d)[128], uint64_t da, uint64_t db, int scale_d) {
  asm volatile("{\n.reg .pred p;\nsetp.ne.b32 p, %130, 0;\nwgmma.mma_async.sync.aligned.m64n256k16.f32.bf16.bf16 " ACC128
               " %128, %129, p, 1, 1, 0, 0;\n}\n" : R128(d) : "l"(da), "l"(db), "r"(scale_d));
}
DEVI void wgmma_n256_rs(float (&d)[128], uint32_t a0, uint32_t a1, uint32_t a2, uint32_t a3, uint64_t db) {
  asm volatile("wgmma.mma_async.sync.aligned.m64n256k16.f32.bf16.bf16 " ACC128 " {%128, %129, %130, %131}, %132, 1, 1, 1, 0;\n"
               : R128(d) : "r"(a0), "r"(a1), "r"(a2), "r"(a3), "l"(db));
}

#define ACC64 \
      "{%0,%1,%2,%3,%4,%5,%6,%7,%8,%9,%10,%11,%12,%13,%14,%15,%16,%17,%18,%19,%20,%21,%22,%23,%24,%25,%26,%27,%28,%29,%30,%31," \
      "%32,%33,%34,%35,%36,%37,%38,%39,%40,%41,%42,%43,%44,%45,%46,%47,%48,%49,%50,%51,%52,%53,%54,%55,%56,%57,%58,%59,%60,%61,%62,%63},"
template <int O> DEVI void wgmma_n128(float (&d)[128], uint64_t da, uint64_t db) {
  asm volatile("wgmma.mma_async.sync.aligned.m64n128k16.f32.bf16.bf16 " ACC64 " %64, %65, 1, 1, 1, 0, 0;\n"
               : R8(d, O), R8(d, O + 8), R8(d, O + 16), R8(d, O + 24), R8(d, O + 32), R8(d, O + 40), R8(d, O + 48), R8(d, O + 56)
               : "l"(da), "l"(db));
}

DEVI void wait_out_init(uint32_t tag) {
  uint32_t it = 0;
  while ((int32_t)(ld_acquire(&g_ctr) - tag) < 0) { if (++it > (1u << 20)) __trap(); }
}
template <int N> DEVI void cp_wait() { asm volatile("cp.async.wait_group %0;" ::"n"(N) : "memory"); }

DEVI int other_chunk(int m, int j) { return m + (m >= j); }
DEVI int p2_col(int n, int j) {
  const int m = n < 18 ? n - 11 : (n - 18) >> 1;
  const int slab = n < 18 ? 1 : 2 + (n & 1);
  return other_chunk(m, j) * 256 + slab * 64;
}

__global__ void __cluster_dims__(2, 1, 1) __launch_bounds__(384, 1)
fused_kernel(const __nv_bfloat16* __restrict__ x, const __nv_bfloat16* __restrict__ wd_re, const __nv_bfloat16* __restrict__ wd_im,
             const __nv_bfloat16* __restrict__ w_r, const __nv_bfloat16* __restrict__ w_gate, const __nv_bfloat16* __restrict__ w_up,
             const __grid_constant__ Maps maps, const __nv_bfloat16* __restrict__ w_down, __nv_bfloat16* __restrict__ out) {
  extern __shared__ __align__(1024) uint8_t smem[];
  const uint32_t rank = blockIdx.x & 1;
  const uint32_t base = smem_u32(smem);
  uint8_t* aux = smem + OFF_AUX;
  const uint32_t auxs = base + OFF_AUX;
  const uint32_t full0 = auxs + OFF_BAR, empty0 = full0 + 8 * STAGES, bar_stat = empty0 + 8 * STAGES, bar_ab = bar_stat + 8,
                 bar_out = bar_ab + 32, bar_pub = bar_out + 64, bar_gu = bar_pub + 16;
  const uint32_t kcur = auxs + OFF_MISC + 16;

  const int tid = threadIdx.x, lane = tid & 31;
  if (tid == 256) TL(0);
  const int cl = blockIdx.x >> 1;
  const int pos = cl - 4 + max(((cl - 29) * 37) >> 8, 0) + ((cl - 4) >> 31 & (7 * cl + 36));
  const int j = (~pos & 3) * 2 + (pos >> 5), half = (pos >> 2) & 1, eb = (((pos >> 3) + (pos >> 5)) & 3) * 2 + rank;
  {
    const uint32_t dst = base + (tid >> 3) * 128 + (((tid ^ (tid >> 3)) & 7) << 4);
    const char* pa = (const char*)x + (uint32_t)((half * 1024 + j * 64 + (tid >> 3)) * (D_ * 2) + (tid & 7) * 16);
    const uint32_t off = (eb * 64 + (tid >> 4) + (tid & 8) * 64) * (D_ * 2) + (tid & 7) * 16;
    if (tid < 256) {
#pragma unroll
      for (int q = 0; q < 12; q++)
        cp_async16(dst + (q < 4 ? q * 4096 : OFF_B + (q - 4) * 4096),
                   q < 4 ? pa + ((q & 1) * 32 + (q >> 1) * 512) * (D_ * 2) : (const char*)(q < 8 ? wd_re : wd_im) + off + (q & 3) * (16 * D_ * 2));
      asm volatile("cp.async.commit_group;" ::: "memory");
    }
    if (tid == 0) TL(15);
  }
  const int warp = __shfl_sync(0xffffffffu, tid >> 5, 0);
  const int bid = j * 16 + half * 8 + eb;
  const __nv_bfloat16* wd_rows = (bid < 64 ? wd_re : wd_im) + (size_t)(bid & 63) * 16 * D_;
  if (warp == 9) ((uint4*)(aux + OFF_FLAGS))[lane] = make_uint4(0, 0, 0, 0);
  if (tid == 256) {
    prefetch_map(&maps.x);
    prefetch_map(&maps.wd[0]);
    prefetch_map(&maps.wd[1]);
    if (base != (rank << 24) + SM0) __trap();
#pragma unroll
    for (int s = 0; s < STAGES; s++) { mbar_init(full0 + 8 * s, 1); mbar_init(empty0 + 8 * s, 2); }
    mbar_init(bar_stat, 3);
#pragma unroll
    for (int s = 0; s < 4; s++) mbar_init(bar_ab + 8 * s, 4);
    mbar_init(bar_pub, 1);
    mbar_init(bar_pub + 8, 2);
    mbar_init(bar_gu, 1);
    mbar_init(bar_pub + 24, 1);
    sts32(kcur, 0);
    mbar_init(bar_out, 1);
    mbar_init(bar_out + 8, 1);
    asm volatile("fence.mbarrier_init.release.cluster;" ::: "memory");
  }
  __syncthreads();
  asm volatile("barrier.cluster.arrive.relaxed.aligned;" ::: "memory");
  asm volatile("barrier.cluster.wait.acquire.aligned;" ::: "memory");

  if (warp == 8) {
    if (elect_one()) {
      const int arow = eb * 128;
      int pf_i = 0;
      auto prefetch_ws = [&](int k) {
        if ((WS_MASK >> k) & 1) {
          const int q = pf_i < 4 ? pf_i : pf_i < 10 ? pf_i >= 7 : 2 + (pf_i & 1);
          const int c = pf_i < 4 ? j >> 1 : other_chunk(pf_i < 7 ? pf_i - 4 : pf_i < 10 ? pf_i - 7 : (pf_i - 10) >> 1, j >> 1);
          tma_prefetch(&maps.ws_pf[q & 1], half * 1024 + (q & 2) * 256 + c * 128, (j * 8 + eb) * (PR / 8));
          pf_i++;
        }
      };
      auto ws_col = [&](int col) { return half * 1024 + (col & 128) * 4 + (col >> 8) * 64; };
      auto load_b = [&](int st, int col) { tma_load5(base + OFF_B + st * B_BYTES, &maps.ws[(col >> 6) & 1], ws_col(col), j * PR, full0 + 8 * st); };
      TL(1);
#pragma unroll 1
      for (int k = CP0; k < K1 + 2; k++) {
        const int st = k & 3;
        mbar_wait(empty0 + 8 * st, ((k >> 2) & 1) ^ 1);
        TKP(2, k);
        if (k < K1) {
          mbar_expect_tx(full0 + 8 * st, A_BYTES + B_BYTES);
          tma_load3(base + st * A_BYTES, &maps.x, k * 64, j * 64, half * 2, full0 + 8 * st);
          tma_load3(base + OFF_B + st * B_BYTES, &maps.wd[0], k * 64, 0, eb * 64, full0 + 8 * st);
          tma_load3(base + OFF_B + st * B_BYTES + B_BYTES / 2, &maps.wd[1], k * 64, 0, eb * 64, full0 + 8 * st);
        } else {
          mbar_expect_tx(full0 + 8 * st, B_BYTES);
          load_b(st, j * 256 + (k - K1) * 64);
        }
        sts32(kcur, k);
        if (k == 4) { prefetch_l2(wd_rows, 16 * D_ * 2); prefetch_map(&maps.ws[0]); prefetch_map(&maps.ws[1]); prefetch_map(&maps.ws_pf[0]); prefetch_map(&maps.ws_pf[1]); prefetch_map(&maps.ab_ld); prefetch_map(&maps.ab_st); }
        prefetch_ws(k);
      }
      mbar_wait(bar_stat, 0);
      const uint32_t tag = lds32(auxs + OFF_MISC);
      uint32_t* flags = g_abflag + (eb * 2 + half) * 96;
      auto put = [&](int h) {
        tma_store(&maps.ab_st, base + h * (A_BYTES / 2), j * 256 + (h >> 1) * 64, half * 1024 + arow + (h & 1) * 64);
        bulk_commit();
      };
      auto own_b = [&](int q) {
        mbar_wait(empty0 + 8 * q, 1);
        TKP(2, K1 + q);
        sts32(kcur, K1 + q);
        mbar_expect_tx(full0 + 8 * q, B_BYTES);
        load_b(q, j * 256 + q * 64);
      };
      mbar_wait(bar_ab + 8, 0);
      fence_proxy_async_smem();
      put(0);
      mbar_wait(bar_ab, 0);
      put(1);
      TL(8);
      own_b(2);
      bulk_wait<0>();
      TL(11);
      mbar_arrive(bar_pub + 24);
      own_b(3);
      const uint32_t mirror = auxs + OFF_FLAGS;
      uint32_t mc = 0;
      auto refresh = [&](int lv) {
        cp_async16(mirror + mc + lv * 32, flags + lv * 32);
        cp_async16(mirror + mc + lv * 32 + 16, flags + lv * 32 + 4);
        mc = (mc + 128) & (NMIR * 128 - 1);
      };
      auto ready = [&](int f) {
        uint32_t v[NMIR];
#pragma unroll
        for (int i = 0; i < NMIR; i++) v[i] = lds32(mirror + f * 4 + i * 128);
        bool r = false;
#pragma unroll
        for (int i = 0; i < NMIR; i++) r |= v[i] == tag;
        return r;
      };
      auto level_set = [&](int lv) {
        bool r = false;
#pragma unroll
        for (int i = 0; i < NMIR; i++) {
          const uint4 u = lds128(mirror + i * 128 + lv * 32), v = lds128(mirror + i * 128 + lv * 32 + 16);
          r |= ((u.x ^ tag) | (u.y ^ tag) | (u.z ^ tag) | (u.w ^ tag) | (v.x ^ tag) | (v.y ^ tag) | (v.z ^ tag) | (v.w ^ tag)) == 0;
        }
        return r;
      };
      auto wait_level = [&](int lv) {
        uint32_t it = 0;
        while (!level_set(lv)) {
          refresh(lv);
          if (++it > (1u << 20)) __trap();
          __nanosleep(150);
        }
      };
      auto load_a = [&](int st, uint32_t dst, int col) { tma_load(dst, &maps.ab_ld, col, half * 1024 + arow, full0 + 8 * st); };
      mbar_wait(bar_ab + 16, 0);
      mbar_wait(bar_ab + 24, 0);
      fence_proxy_async_smem();
      refresh(0);
      {
        uint32_t it = 0;
        while (!mbar_test(empty0, 0)) {
          __nanosleep(150);
          refresh(0);
          if (++it > (1u << 20)) __trap();
        }
      }
      uint32_t seen = 0;
      bool ahead = false;
      auto issue_b = [&](int n) {
        TKP(2, K1 + n);
        mbar_expect_tx(full0 + 8 * (n & 3), A_BYTES + B_BYTES);
        load_b(n & 3, other_chunk(n - 4, j) * 256);
      };
      auto try_ahead = [&](int n) {
        if (n < 7 && !ahead && mbar_test(empty0 + 8 * (n - 3), 0)) { issue_b(n + 1); ahead = true; }
      };
#pragma unroll 1
      for (int n = 4; n < 11; n++) {
        const int k = K1 + n, st = k & 3;
        const int c = other_chunk(n - 4, j);
        if (!ahead) {
          mbar_wait(empty0 + 8 * st, ((k >> 2) & 1) ^ 1);
          issue_b(n);
        }
        ahead = false;
        if (n == 4) put(4);
        uint32_t it = 3;
        while (!(seen & 1) && !ready(c)) {
          if ((++it & 3) == 0) refresh(0);
          if (it > (1u << 22)) __trap();
          try_ahead(n);
        }
        if (n == 5) mbar_wait(bar_pub, 0);
        if (n == 6) bulk_wait_read<1>();
        if (n == 7) { bulk_wait<0>(); mbar_arrive(bar_pub + 8); TL(23); }
        TKP(3, k);
        load_a(st, base + st * A_BYTES, c * 256);
        try_ahead(n);
        if (n < 7) put(n + 1);
        sts32(kcur, k);
        seen >>= 1;
        if (n < 9) {
          if (ready(other_chunk(n - 2, j))) seen |= 2;
          else refresh(0);
        }
        if (n == 8) refresh(1);
      }
#pragma unroll 1
      for (int k = K1 + 11; k < KT - 3; k++) {
        const int st = k & 3, col = p2_col(k - K1, j);
        if (k == K1 + 11 || k == K1 + 18) wait_level(k == K1 + 11 ? 1 : 2);
        mbar_wait(empty0 + 8 * st, ((k >> 2) & 1) ^ 1);
        TKP(2, k);
        mbar_expect_tx(full0 + 8 * st, A_BYTES + B_BYTES);
        load_b(st, col);
        load_a(st, base + st * A_BYTES, col);
        sts32(kcur, k);
        if (k == K1 + 15) refresh(2);
        prefetch_ws(k);
        if (k == K1 + 20) { prefetch_map(&maps.ws_h[0]); prefetch_map(&maps.ws_h[1]); prefetch_map(&maps.out); }
      }
      const int c1 = p2_col(K2 - 3, j), c2 = p2_col(K2 - 2, j), c3 = c2 + 64;
      auto load_h = [&](int hs, int col, int h, int st) {
        tma_load5(base + OFF_B + hs * (B_BYTES / 2), &maps.ws_h[(col >> 6) & 1], ws_col(col), j * PR + h * (PR / 2), full0 + 8 * st);
      };
      mbar_wait(empty0 + 8, 0);
      TKP(2, KT - 3);
      mbar_expect_tx(full0 + 8, A_BYTES + B_BYTES);
      load_h(2, c1, 0, 1);
      load_a(1, base + A_BYTES, c1);
      load_a(1, base + OFF_B + 3 * (B_BYTES / 2), c3);
      sts32(kcur, KT - 3);
      wait_out_init(tag);
      mbar_arrive(bar_out + 8);
      mbar_wait(empty0 + 16, 0);
      TKP(2, KT - 2);
      mbar_expect_tx(full0 + 16, A_BYTES + B_BYTES);
      load_h(4, c2, 0, 2);
      load_a(2, base + 2 * A_BYTES, c2);
      load_h(5, c3, 0, 2);
      mbar_wait(empty0 + 24, 0);
      TKP(2, KT - 1);
      mbar_expect_tx(full0 + 24, B_BYTES);
      load_h(6, c1, 1, 3);
      load_h(7, c2, 1, 3);
      mbar_wait(empty0, 1);
      TL(17);
      mbar_expect_tx(full0, B_BYTES / 2);
      load_h(0, c3, 1, 0);
      asm volatile("cp.async.wait_all;" ::: "memory");
    }
  } else if (warp > 8) {
    const int t = tid - 288, w = warp - 9;
    float2* xs = (float2*)(aux + OFF_XS);
    float* red = (float*)(aux + OFF_RED);
    volatile uint32_t* misc = (volatile uint32_t*)(aux + OFF_MISC);

    const uint32_t ring = auxs + OFF_RING + (t >> 5) * 8192 + lane * 16;
    auto fetch_to = [&](uint32_t dst, const __nv_bfloat16* src, auto stepc, bool on) {
      if (on) {
#pragma unroll
        for (int k = 0; k < 4; k++) {
          if (decltype(stepc)::value == 256) cp_async16(dst + k * 512, src + k * 256);
          else cp_async16_once(dst + k * 512, src + k * decltype(stepc)::value);
        }
      }
      asm volatile("cp.async.commit_group;" ::: "memory");
    };
    auto fetch = [&](int slot, const __nv_bfloat16* src, auto stepc, bool on) { fetch_to(ring + slot * 2048, src, stepc, on); };
    const int nrow = w ? 5 : 6, lrow0 = w ? 1 + 5 * w : 0;
    const int row0 = bid * 16 + lrow0;
    const __nv_bfloat16* xrow = x + (size_t)row0 * D_ + lane * 8;
    const __nv_bfloat16* wrow = wd_rows + lrow0 * D_ + lane * 8;
    const int slot4 = (OFF_XS - OFF_RING) / 2048 - 4 * w + (w ? w - 1 : 2);
    auto pace = [&](int k) {
      uint32_t it = 0;
      while ((int)lds32(kcur) < k) {
        if (++it > (1u << 20)) __trap();
        __nanosleep(50);
      }
    };
    auto fetch_row = [&](const __nv_bfloat16* p, int i) { fetch(i < 4 ? i : slot4 + i - 4, p + i * D_, IC<256>{}, i < nrow); };
    auto load_row = [&](int i, uint32_t (&xv)[16]) {
      const uint32_t a = ring + (i < 4 ? i : slot4 + i - 4) * 2048;
#pragma unroll
      for (int k = 0; k < 4; k++) {
        const uint4 v = lds128(a + k * 512);
        xv[4 * k] = v.x; xv[4 * k + 1] = v.y; xv[4 * k + 2] = v.z; xv[4 * k + 3] = v.w;
      }
    };
    mbar_wait(full0, 0);
    if (w == 0) asm volatile("prefetch.global.L2 [%0];" ::"l"(wd_rows + (lane >> 1) * D_ + (4 + (lane & 1)) * 64) : "memory");
#pragma unroll
    for (int i = 0; i < 3; i++) fetch_row(xrow, i);
    const uint32_t tag = (ld_relaxed(&g_ctr) & ~(uint32_t)(NCTA - 1)) + NCTA;
    const uint32_t tag16 = (tag >> 7) & 0xffffu, tag5 = (tag16 & 31u) << 11;
    uint32_t xo[6][16];
    auto store_row = [&](int i) {
#pragma unroll
      for (int k = 0; k < 4; k++)
        *(uint4*)(out + (size_t)(row0 + i) * D_ + lane * 8 + k * 256) = make_uint4(xo[i][4 * k], xo[i][4 * k + 1], xo[i][4 * k + 2], xo[i][4 * k + 3]);
    };
    {
      uint4 wv4[4];
#pragma unroll
      for (int k = 0; k < 4; k++) wv4[k] = __ldg((const uint4*)(w_r + lane * 8 + k * 256));
      float sh[8];
      const int ri = nrow - 1 - (lane & 7);
      float wr[32];
      float wrsum = 0.f;
#pragma unroll
      for (int k = 0; k < 4; k++) {
        const uint32_t wv[4] = {wv4[k].x, wv4[k].y, wv4[k].z, wv4[k].w};
#pragma unroll
        for (int c = 0; c < 4; c++) {
          wr[8 * k + 2 * c] = bf_lo(wv[c]);
          wr[8 * k + 2 * c + 1] = bf_hi(wv[c]);
          wrsum += wr[8 * k + 2 * c] + wr[8 * k + 2 * c + 1];
        }
      }
      wrsum = warp_sum(wrsum);
#pragma unroll
      for (int q = 0; q < 8; q++) sh[q] = 0.f;
#pragma unroll 1
      for (int i = 0; i < nrow; i++) {
        uint32_t xv[16];
        if (i + 3 < nrow) pace(LN_K0 + i);
        fetch_row(xrow, i + 3);
        cp_wait<3>();
        load_row(i, xv);
        float s0 = 0.f, s1 = 0.f, q0 = 0.f, q1 = 0.f, r0 = 0.f, r1 = 0.f;
#pragma unroll
        for (int c = 0; c < 16; c++) {
          const float a = bf_lo(xv[c]), b = bf_hi(xv[c]);
          s0 += a;
          s1 += b;
          q0 = fmaf(a, a, q0);
          q1 = fmaf(b, b, q1);
          r0 = fmaf(a, wr[2 * c], r0);
          r1 = fmaf(b, wr[2 * c + 1], r1);
        }
        float s[4] = {s0 + s1, q0 + q1, r0 + r1, 0.f};
        xreduce<2, 16>(s, lane);
        xreduce<1, 8>(s, lane);
#pragma unroll
        for (int q = 5; q > 0; q--) sh[q] = sh[q - 1];
        sh[0] = s[0];
      }
#pragma unroll
      for (int i = 0; i < 6; i++) load_row(min(i, nrow - 1), xo[i]);
#pragma unroll
      for (int i = 0; i < 6; i++) fetch_row(wrow, i);
      xreduce<4, 4>(sh, lane);
      xreduce<2, 2>(sh, lane);
      xreduce<1, 1>(sh, lane);
      const float mean = __shfl_sync(0xffffffffu, sh[0], lane & 7) * (1.f / D_);
      float var = fmaf(-mean, mean, __shfl_sync(0xffffffffu, sh[0], 8 + (lane & 7)) * (1.f / D_));
      const float dot = __shfl_sync(0xffffffffu, sh[0], 16 + (lane & 7));
      if (__any_sync(0xffffffffu, mean * mean > 16.f * var)) {
#pragma unroll 1
        for (int i = 0; i < nrow; i++) {
          const uint32_t* xv = (const uint32_t*)(x + (size_t)(row0 + i) * D_) + lane;
          const float m = __shfl_sync(0xffffffffu, mean, nrow - 1 - i);
          float qq = 0.f;
#pragma unroll 4
          for (int c = 0; c < 16; c++) {
            const uint32_t v = __ldg(xv + 32 * c);
            const float a = bf_lo(v) - m, b = bf_hi(v) - m;
            qq = fmaf(a, a, fmaf(b, b, qq));
          }
          qq = warp_sum(qq) * (1.f / D_);
          if (ri == i) var = qq;
        }
      }
      const float mb = bf_round(mean);
      const float den = bf_round(sqrt_approx(bf_round(bf_round(var) + 1e-5f)));
      const float inv = rcp_approx(den);
      if (lane < nrow) st_rec(g_stat + row0 + ri, __float_as_uint(inv), __float_as_uint(mb) | tag16);
      const uint32_t u = pack_bf16(0.f, fmaf(-mb, wrsum, dot) * inv);
      const uint32_t key = lane < nrow ? ((u ^ (0x80000000u | (uint32_t)((int32_t)u >> 31))) & 0xffff0000u) | tag5 | (uint32_t)(S_ - 1 - row0 - ri) : 0u;
      const uint32_t k0 = __reduce_max_sync(0xffffffffu, key);
      const uint32_t k1 = __reduce_max_sync(0xffffffffu, key == k0 ? 0u : key);
      if (lane == 0) { st_rec(g_cand + bid * 3 + w, k0, k1); TL(26 + w); }
      const uint32_t mi = pack_bf16(mb, inv);
      auto out_rows = [&](int lo, int hi) {
#pragma unroll
        for (int i = lo; i < hi; i++) {
          const uint32_t mv = __shfl_sync(0xffffffffu, mi, nrow - 1 - i);
          const uint32_t mb2 = __byte_perm(mv, 0, 0x1010), inv2 = __byte_perm(mv, 0, 0x3232);
#pragma unroll
          for (int c = 0; c < 16; c++) xo[i][c] = bf2_fma(bf2_sub(xo[i][c], mb2), inv2, xo[i][c]);
          if (i < NST) store_row(i);
        }
      };
      out_rows(0, NST);
      if (t == 0) TL(16);
#pragma unroll
      for (int q = 0; q < 8; q++) sh[q] = 0.f;
#pragma unroll 1
      for (int i0 = 0; i0 < 6; i0 += 2) {
        uint32_t xv[2][16];
        cp_wait<4>();
        asm volatile("cp.async.commit_group;\ncp.async.commit_group;" ::: "memory");
        load_row(i0, xv[0]);
        load_row(min(i0 + 1, nrow - 1), xv[1]);
        float s0 = 0.f, s1 = 0.f, s2 = 0.f, s3 = 0.f;
#pragma unroll
        for (int c = 0; c < 16; c++) { s0 += bf_lo(xv[0][c]); s1 += bf_hi(xv[0][c]); s2 += bf_lo(xv[1][c]); s3 += bf_hi(xv[1][c]); }
#pragma unroll
        for (int q = 5; q > 1; q--) sh[q] = sh[q - 2];
        sh[1] = s0 + s1;
        sh[0] = s2 + s3;
      }
      xreduce<4, 4>(sh, lane);
      xreduce<2, 2>(sh, lane);
      xreduce<1, 1>(sh, lane);
      sh[0] += __shfl_xor_sync(0xffffffffu, sh[0], 8);
      sh[0] += __shfl_xor_sync(0xffffffffu, sh[0], 16);
      const float wv = -sh[0], hi = bf_hi(__float_as_uint(wv)), mid = bf_hi(__float_as_uint(wv - hi));
      if (lane < 6 && 5 - lane < nrow)
        st_rec(g_wsum + row0 + 5 - lane, __byte_perm(__float_as_uint(hi), __float_as_uint(mid), 0x7632), __byte_perm(__float_as_uint(wv - hi - mid), tag16, 0x5432));
      if (t == 0) TL(7);
      out_rows(NST, 6);
    }
    const int nblk = bid < NFFN ? (w ? (32 - NB0) / 2 : NB0) : 0, blk0 = w ? NB0 + (w - 1) * ((32 - NB0) / 2) : 0;
    if (t == 0) TL(2);
    const size_t guoff = (size_t)(rank * 512 + 16 * blk0 + (lane >> 3)) * F_ + (bid >> 1) * 64 + (lane & 7) * 8;
    const __nv_bfloat16 *pg = w_gate + guoff, *pu = w_up + guoff;
    auto fill = [&]() {
      pace(GU_KF);
      fetch(0, pg, IC<4 * F_>{}, nblk);
      fetch(1, pu, IC<4 * F_>{}, nblk);
      fetch(2, pg + 16 * F_, IC<4 * F_>{}, nblk);
      fetch(3, pu + 16 * F_, IC<4 * F_>{}, nblk);
#pragma unroll
      for (int i = NST; i < 5; i++) store_row(i);
      if (w == 0) store_row(5);
    };
    if (w == 0) {
      uint2 ws[8];
      uint32_t it = 0, bad;
      auto load_ws = [&]() {
#pragma unroll
        for (int i = 0; i < 8; i++) ws[i] = ld_rec(g_wsum + eb * 64 + (lane >> 1) + (lane & 1) * 512 + (i & 3) * 16 + (i >> 2) * 1024);
      };
      load_ws();
      if (lane == 0) misc[0] = tag;
      while (true) {
        bad = 0;
#pragma unroll
        for (int i = 0; i < 8; i++) bad |= (ws[i].y >> 16) ^ tag16;
        if (!poll_again(bad, it)) break;
        load_ws();
      }
#pragma unroll
      for (int i = 0; i < 8; i++) ((uint4*)(aux + OFF_WSUM))[32 * i + lane] = make_uint4(ws[i].x, ws[i].y & 0xffffu, 0u, 0u);
      fence_proxy_async_smem();
      __syncwarp();
      if (lane == 0) { mbar_arrive(bar_stat); TL(3); }
      fill();
    } else {
      uint4 kv[6], cs;
      uint32_t it = 0, bad;
      do {
        cs = ld_rec2(g_stat + half * 1024 + (w - 1) * 512 + j * 64 + 2 * lane);
        bad = ((cs.y ^ tag16) | (cs.w ^ tag16)) & 0xffffu ? 0xf800u : 0u;
#pragma unroll
        for (int i = 0; i < 6; i++) kv[i] = ld_rec2(g_cand + 2 * lane + 64 * i);
#pragma unroll
        for (int i = 0; i < 6; i++) bad |= (kv[i].x ^ tag5) | (kv[i].z ^ tag5);
      } while (poll_again(bad & 0xf800u, it));
      ((uint4*)(aux + OFF_STAT))[t - 32] = make_uint4(cs.x, __byte_perm(cs.y, 0, 0x3232), cs.z, __byte_perm(cs.w, 0, 0x3232));
      __syncwarp();
      if (lane == 0) mbar_arrive(bar_stat);
      uint32_t k0 = 0, k1 = 0;
#pragma unroll
      for (int i = 0; i < 6; i++) {
        const uint32_t c0 = max(kv[i].x, kv[i].z), c1 = max(min(kv[i].x, kv[i].z), max(kv[i].y, kv[i].w));
        k1 = max(max(k1, c1), min(k0, c0));
        k0 = max(k0, c0);
      }
      const uint32_t m0 = __reduce_max_sync(0xffffffffu, k0);
      const uint32_t m1 = __reduce_max_sync(0xffffffffu, k0 == m0 ? k1 : k0);
      if (t == 32) { misc[2] = m0; misc[3] = m1; }
      {
        const int r0 = S_ - 1 - (m0 & (S_ - 1)), r1 = S_ - 1 - (m1 & (S_ - 1));
        const uint32_t* pa = (const uint32_t*)(x + (size_t)r0 * D_ + rank * 512 + (w - 1) * 256) + lane;
        const uint32_t* pb = (const uint32_t*)(x + (size_t)r1 * D_ + rank * 512 + (w - 1) * 256) + lane;
        uint32_t xa[4], xb[4];
#pragma unroll
        for (int k = 0; k < 4; k++) { xa[k] = ld_relaxed(pa + 32 * k); xb[k] = ld_relaxed(pb + 32 * k); }
        uint2 sa = ld_rec(g_stat + r0), sb = ld_rec(g_stat + r1);
        fill();
        while (poll_again(((sa.y ^ tag16) | (sb.y ^ tag16)) & 0xffffu, it)) {
          sa = ld_rec(g_stat + r0);
          sb = ld_rec(g_stat + r1);
        }
        const uint32_t ma = __byte_perm(sa.y, 0, 0x3232), mb = __byte_perm(sb.y, 0, 0x3232);
        const float ia = __uint_as_float(sa.x), ib = __uint_as_float(sb.x);
#pragma unroll
        for (int k = 0; k < 4; k++) {
          const uint32_t da = bf2_sub(xa[k], ma), db = bf2_sub(xb[k], mb);
          const uint32_t na = pack_bf16(bf_lo(da) * ia, bf_hi(da) * ia), nb = pack_bf16(bf_lo(db) * ib, bf_hi(db) * ib);
          ((float4*)xs)[(w - 1) * 128 + 32 * k + lane] = make_float4(bf_lo(na), bf_lo(nb), bf_hi(na), bf_hi(nb));
        }
      }
    }
    named_bar(1, 96);
    if (t == 0) TL(4);
    if (t == 32) {
      mbar_wait(bar_ab + 16, 0);
      fence_proxy_async_smem();
      mbar_wait(bar_pub + 24, 0);
      tma_store(&maps.ab_ld, base + A_BYTES, j * 256 + 64, half * 1024 + eb * 128);
      bulk_commit();
      mbar_wait(bar_ab + 24, 0);
      mbar_arrive_cluster(bar_pub + 8, rank ^ 1);
      bulk_wait<0>();
      mbar_arrive(bar_pub);
    }
    if (t == 0) {
      auto flag = [&](int lv) {
        fence_gpu();
        st_relaxed(g_abflag + (eb * 2 + half) * 96 + lv * 32 + j, tag);
      };
      mbar_wait(bar_pub + 24, 0);
      flag(0);
      TL(9);
      mbar_wait(bar_pub, 0);
      flag(1);
      asm volatile("red.relaxed.gpu.global.add.u32 [%0], 1;" ::"l"(&g_ctr) : "memory");
      TL(19);
      mbar_wait(bar_pub + 8, 0);
      flag(2);
      TL(22);
    }
    __syncwarp();
    const int cb = bid & 15, kg = bid >> 4;
    const int ndn = w ? 9 : 10;
    const __nv_bfloat16* pd = w_down + (size_t)(kg * 448 + 16 * w + (lane >> 3)) * D_ + cb * 64 + (lane & 7) * 8;
    uint32_t sa = ring;
    uint4 v0[4], v1[4];
    float2 xv[4] = {};
    auto take = [&](uint4 (&v)[4]) {
      cp_wait<3>();
#pragma unroll
      for (int i = 0; i < 4; i++) v[i] = lds128(sa + i * 512);
    };
    auto next_down = [&](bool on) {
      fetch_to(sa, pd, IC<4 * D_>{}, on);
      pd += 48 * D_;
    };
    auto gemv16 = [&](float (&acc)[16], const uint4 (&v)[4], int h) {
      gemv8(acc, v[2 * h], xv[2 * h]);
      gemv8(acc, v[2 * h + 1], xv[2 * h + 1]);
    };
    if (nblk) {
      float ag[16], au[16];
#pragma unroll
      for (int i = 0; i < 16; i++) { ag[i] = 0.f; au[i] = 0.f; }
      const float2* xp = xs + 16 * blk0 + (lane >> 3);
      int kq = 2 * GU_K1;
      auto refill = [&](int kc, const __nv_bfloat16* p, bool gu) {
        if (kc < (kq >> 1)) pace(kq >> 1);
        kq += kq < 2 * GU_K0 ? 2 : 1;
        if (gu) fetch_to(sa, p, IC<4 * F_>{}, true);
        else next_down(true);
        sa = ring + ((sa - ring + 2048) & 8191);
      };
      take(v0);
      xv[0] = xp[0];
      xv[1] = xp[4];
      pg += 32 * F_;
      pu += 32 * F_;
      refill(0, pg, true);
#pragma unroll 1
      for (int b = 0; b < nblk; b++) {
        take(v1);
        int kc = lds32(kcur);
        xv[2] = xp[8];
        xv[3] = xp[12];
        xp += 16;
        pg += 16 * F_;
        gemv16(ag, v0, 0);
        refill(kc, pu, b + 2 < nblk);
        gemv16(ag, v0, 1);
        take(v0);
        kc = lds32(kcur);
        pu += 16 * F_;
        gemv16(au, v1, 0);
        xv[0] = xp[0];
        xv[1] = xp[4];
        refill(kc, pg, b + 3 < nblk);
        gemv16(au, v1, 1);
      }
      float s[32];
#pragma unroll
      for (int i = 0; i < 16; i++) { s[i] = ag[i]; s[16 + i] = au[i]; }
      xreduce<16, 16>(s, lane);
      xreduce<8, 8>(s, lane);
      mbar_wait(bar_pub + 8, 0);
      const uint32_t dst = mapa(auxs + OFF_GU + (rank * 3 + w) * 512 + (lane >> 4) * 256 + (lane & 3) * 64 + (lane & 8) * 4, (lane >> 2) & 1);
      const uint32_t dbar = mapa(bar_gu, (lane >> 2) & 1);
      st_async4(dst, s[0], s[1], s[2], s[3], dbar);
      st_async4(dst + 16, s[4], s[5], s[6], s[7], dbar);
      if (w == 0) {
        if (lane == 0) mbar_expect_tx(bar_gu, 6 * 512);
        mbar_wait(bar_gu, 0);
        const float2* r2 = (const float2*)(aux + OFF_GU) + lane;
        float2 g2 = r2[0], u2 = r2[32];
#pragma unroll
        for (int q = 1; q < 6; q++) {
          const float2 a = r2[64 * q], c = r2[64 * q + 32];
          g2.x += a.x; g2.y += a.y; u2.x += c.x; u2.y += c.y;
        }
        float hv[2];
#pragma unroll
        for (int tok = 0; tok < 2; tok++) {
          const float g = bf_round(tok ? g2.y : g2.x), u = bf_round(tok ? u2.y : u2.x);
          hv[tok] = bf_round(__fdividef(g, 1.f + __expf(-g))) * u;
        }
        st_rec(g_h + bid * 32 + lane, pack_bf16(hv[0], hv[1]), tag);
        if (lane == 0) TL(5);
      }
    } else {
#pragma unroll
      for (int u = 0; u < 4; u++) fetch(u, pd + u * 48 * D_, IC<4 * D_>{}, true);
      pd += 4 * 48 * D_;
      take(v0);
      next_down(true);
      sa += 2048;
      pace(H_K);
    }
    if (t == 32) wait_out_init(tag);
    named_bar(1, 96);
    {
      uint4 hv[3];
      uint32_t it = 0;
      bool bad[3] = {true, true, w == 0};
      while (true) {
#pragma unroll
        for (int i = 0; i < 3; i++) if (bad[i]) hv[i] = ld_rec2(g_h + kg * 448 + 2 * (t + 96 * i));
#pragma unroll
        for (int i = 0; i < 3; i++) bad[i] = bad[i] && (hv[i].y != tag || hv[i].w != tag);
        if (!poll_again(bad[0] || bad[1] || bad[2], it)) break;
        __nanosleep(100);
      }
#pragma unroll
      for (int i = 0; i < 3; i++) {
        if (t + 96 * i < 224) ((float4*)xs)[t + 96 * i] = make_float4(bf_lo(hv[i].x), bf_hi(hv[i].x), bf_lo(hv[i].z), bf_hi(hv[i].z));
      }
    }
    named_bar(1, 96);
    if (t == 0) TL(10);
    {
      float ay[16];
#pragma unroll
      for (int q = 0; q < 16; q++) ay[q] = 0.f;
      const float2* hp = xs + 16 * w + (lane >> 3);
      xv[0] = hp[0];
      xv[1] = hp[4];
      auto unit = [&](const uint4 (&v)[4], uint4 (&vn)[4], int u) {
        take(vn);
        xv[2] = hp[8];
        xv[3] = hp[12];
        hp += 48;
        gemv16(ay, v, 0);
        xv[0] = hp[0];
        xv[1] = hp[4];
        next_down(u + 5 < ndn);
        sa = ring + ((sa - ring + 2048) & 8191);
        gemv16(ay, v, 1);
      };
#pragma unroll 1
      for (int u = 0; u < ndn; u += 2) {
        unit(v0, v1, u);
        if (u + 1 < ndn) unit(v1, v0, u + 1);
      }
      xreduce<8, 16>(ay, lane);
      xreduce<4, 8>(ay, lane);
      ((float4*)red)[w * 32 + (lane & 7) * 4 + (lane >> 3)] = make_float4(ay[0], ay[1], ay[2], ay[3]);
    }
    named_bar(1, 96);
    if (t < 64) {
      const float* r = red + 4 * lane + w;
      const uint32_t key = misc[2 + w];
      const uint32_t rb = (key ^ (0x80000000u | ~(uint32_t)((int32_t)key >> 31))) & 0xffff0000u;
      const float gate = bf_round(__fdividef(1.f, 1.f + __expf(-__uint_as_float(rb))));
      const uint32_t v = pack_bf16((r[0] + r[128] + r[256]) * gate, (r[2] + r[130] + r[258]) * gate);
      asm volatile("red.relaxed.gpu.global.add.noftz.bf16x2 [%0], %1;"
                   ::"l"(out + (size_t)(S_ - 1 - (key & (S_ - 1))) * D_ + cb * 64 + 2 * lane), "r"(v) : "memory");
      if (t == 0) TL(6);
    }
  } else {
    float acc[128];
    const int wg = warp >> 2, wi = warp & 3;
    const bool elect = (tid & 127) == 0;
    const uint32_t a_base = base + wg * (A_BYTES / 2);

    auto release = [&](int k) {
      if (elect) mbar_arrive(empty0 + 8 * (k & 3));
    };
    const int tw = wg ^ 1;
    auto mma_step = [&](int st, int scale_d, int flip = 0) {
      const uint64_t da = make_desc(SM0 + (wg ^ flip) * (A_BYTES / 2) + st * A_BYTES), db = make_desc(SM0 + OFF_B + st * B_BYTES);
      wgmma_fence();
      wgmma_n256(acc, da, db, scale_d);
      wgmma_n256(acc, da + 2, db + 2, 1);
      wgmma_n256(acc, da + 4, db + 4, 1);
      wgmma_commit();
      wgmma_n256(acc, da + 6, db + 6, 1);
      wgmma_commit();
    };
    auto stamp = [&](int k) {
      if (elect) TK(wg, k);
    };

    {
      const uint32_t dst = (rank << 24) + SM0 + (tid >> 3) * 128 + (((tid ^ (tid >> 3)) & 7) << 4);
      const char* pa = (const char*)x + (uint32_t)((half * 1024 + j * 64 + (tid >> 3)) * (D_ * 2) + (tid & 7) * 16 + 128);
      const uint32_t off = (eb * 64 + (tid >> 4) + (tid & 8) * 64) * (D_ * 2) + (tid & 7) * 16 + 128;
#pragma unroll
      for (int q = 0; q < 12; q++)
        cp_async16(dst + (q < 4 ? A_BYTES + q * 4096 : OFF_B + B_BYTES + (q - 4) * 4096),
                   q < 4 ? pa + ((q & 1) * 32 + (q >> 1) * 512) * (D_ * 2) : (const char*)(q < 8 ? wd_re : wd_im) + off + (q & 3) * (16 * D_ * 2));
      asm volatile("cp.async.commit_group;" ::: "memory");
    }
#pragma unroll 1
    for (int k = 0; k < K1 - 2; k++) {
      if (k < CP0) {
        cp_wait<CP0 - 1>();
        asm volatile("cp.async.commit_group;" ::: "memory");
        fence_proxy_async_smem();
        named_bar(4, 256);
        if (tid == 0) mbar_arrive(full0 + 8 * k);
        stamp(k);
      } else {
        stamp(k);
        mbar_wait(full0 + 8 * (k & 3), (k >> 2) & 1);
        TKC(k);
      }
      mma_step(k & 3, k, 1);
      wgmma_wait<2>();
      if (k) release(k - 1);
    }
    {
      uint2 st0, st1;
      auto stats = [&]() {
        mbar_wait(bar_stat, 0);
        st0 = lds64(auxs + OFF_STAT + (tw * 64 + wi * 16 + (lane >> 2)) * 8);
        st1 = lds64(auxs + OFF_STAT + (tw * 64 + wi * 16 + (lane >> 2)) * 8 + 64);
      };
      mbar_wait(full0 + 16, 1);
      if (tw) {
        wgmma_wait<0>();
        release(K1 - 3);
        mbar_wait(full0 + 24, 1);
        stats();
        named_bar(4, 256);
      }
      stamp(K1 - 2);
      mma_step(2, 1, 1);
      if (!tw) {
        wgmma_wait<2>();
        release(K1 - 3);
        mbar_wait(full0 + 24, 1);
      }
      stamp(K1 - 1);
      mma_step(3, 1, 1);
      if (!tw) stats();
      wgmma_fence();
      wgmma_n256_rs(acc, st0.y, st1.y, 0u, 0u, (uint64_t)((SM0 + OFF_AUX + OFF_WSUM) >> 4) | ((uint64_t)8 << 32));
      wgmma_commit();
      if (!tw) named_bar(4, 256);
      const int r8 = (lane & 1) * 4 + ((lane >> 1) & 3);
      const uint32_t dst = __shfl_sync(0xffffffffu, base + tw * 2 * A_BYTES + ((lane >> 4) * 8 + r8) * 128 + (((2 * wi + ((lane >> 3) & 1)) ^ r8) << 4), lane);
      if (tw) mbar_wait(full0, 0);
      wgmma_wait<3>();
      release(K1 - 2);
      wgmma_wait<1>();
      release(K1 - 1);
      if (tw) mbar_wait(empty0 + 24, 1);
      wgmma_wait<0>();
      if (elect) TL(12 + tw);
#pragma unroll
      for (int p = 0; p < 16; p++) {
        if (p < 8) {
          const float c0 = __uint_as_float(st0.x ^ (p < 4 ? 0 : 0x80000000u)), c1 = __uint_as_float(st1.x ^ (p < 4 ? 0 : 0x80000000u));
#pragma unroll
          for (int i = 16 * p; i < 16 * p + 16; i++) asm volatile("mul.f32 %0, %0, %1;" : "+f"(acc[i]) : "f"(i & 2 ? c1 : c0));
        }
        const float* v = acc + (p & 8) * 8 + (p & 3) * 16 + ((p >> 2) & 1);
        stmatrix_x4_t(dst + p * 2048, pack_bf16(v[0], v[4]), pack_bf16(v[2], v[6]), pack_bf16(v[8], v[12]), pack_bf16(v[10], v[14]));
        if (p == 7 && !tw) {
          mbar_wait(full0, 0);
          fence_proxy_async_smem();
        }
        if (p == 3 || p == 7 || p == 15) {
          __syncwarp();
          if (lane == 0 && (p == 15 || !tw)) mbar_arrive(bar_ab + (p == 3 ? 8 : p == 7 ? 0 : 16 + 8 * tw));
        }
        if (p == 13) {
          mbar_wait(bar_ab, 0);
          mbar_wait(full0 + 8, 0);
        }
      }
      if (elect) TL(29 + tw);
    }
#pragma unroll
    for (int i = 0; i < 128; i++) asm volatile("" : "=f"(acc[i]));
    stamp(K1);
    mma_step(0, 0);
    if (!tw) {
      fence_proxy_async_smem();
      named_bar(2, 128);
    } else {
      mbar_wait(bar_ab + 16, 0);
      fence_proxy_async_smem();
    }
    stamp(K1 + 1);
    mma_step(1, 1);
    wgmma_wait<2>();
    release(K1);
    mbar_wait(bar_ab + 24, 0);
    fence_proxy_async_smem();
#pragma unroll 1
    for (int k = K1 + 2; k < KT - 4; k++) {
      const bool early = k == K1 + 4;
      if (early) {
        wgmma_wait<0>();
        release(k - 1);
      }
      stamp(k);
      mbar_wait(full0 + 8 * (k & 3), (k >> 2) & 1);
      TKC(k);
      mma_step(k & 3, 1);
      wgmma_wait<2>();
      if (!early) release(k - 1);
    }
    const bool second = wg == 0;
    auto turn = [&](auto oc, uint32_t a, int hs) {
      const uint64_t da = make_desc(SM0 + wg * (A_BYTES / 2) + a), db = make_desc(SM0 + OFF_B + hs * (B_BYTES / 2));
      wgmma_fence();
#pragma unroll
      for (int q = 0; q < 4; q++) wgmma_n128<decltype(oc)::value>(acc, da + 2 * q, db + 2 * q);
      wgmma_commit();
    };
    constexpr uint32_t a3 = OFF_B + 3 * (B_BYTES / 2);
    const uint32_t o0 = ((lane >> 4) * 8 + (lane & 7)) * 128 + (((2 * wi + ((lane >> 3) & 1)) ^ (lane & 7)) << 4);
    auto send = [&](auto oc, uint32_t dst, uint32_t pitch) {
      constexpr int O = decltype(oc)::value;
#pragma unroll
      for (int h = 0; h < 2; h++) {
#pragma unroll
        for (int p = 0; p < 4; p++) {
          const float* v = acc + O + 32 * h + 8 * p;
          stmatrix_x4_t(dst + h * pitch + o0 + p * 2048, pack_bf16(v[0], v[1]), pack_bf16(v[2], v[3]), pack_bf16(v[4], v[5]), pack_bf16(v[6], v[7]));
        }
        fence_proxy_async_smem();
        named_bar(2 + wg, 128);
        if (wi == 0 && elect_one()) {
          tma_red_add(&maps.out, dst + h * pitch, eb * 64 + wg * 512, (j * 4 + O / 32 + h) * (PR / 4));
          if (h == 0) TL(24 + (O / 32) + second + 9);
        }
        __syncwarp();
      }
    };
    const float one = __uint_as_float(__shfl_sync(0xffffffffu, lds32(kcur) >> 8, 0) | 0x3f800000u);
    auto cut = [&](int lo) {
#pragma unroll
      for (int i = lo; i < lo + 64; i++) acc[i] *= one;
    };
    mbar_wait(full0, 1);
    wgmma_wait<0>();
    release(KT - 5);
    cut(0);
    if (second) {
      mbar_wait(full0 + 8, 1);
      mbar_wait(full0 + 16, 1);
      named_bar(4, 256);
    }
    stamp(KT - 4);
    turn(IC<0>{}, 0, 0);
    if (!second) mbar_wait(full0 + 8, 1);
    turn(IC<0>{}, A_BYTES, 2);
    if (!second) mbar_wait(full0 + 16, 1);
    turn(IC<0>{}, 2 * A_BYTES, 4);
    wgmma_wait<2>();
    release(0);
    turn(IC<0>{}, a3, 5);
    named_arrive(4 + second, 256);
    stamp(KT - 3);
    if (wi == 0) {
      mbar_wait(bar_out + 8, 0);
      fence_proxy_async();
    }
    mbar_wait(second ? bar_out : empty0 + 24, 0);
    wgmma_wait<2>();
    if (second) named_bar(2 + wg, 128);
    wgmma_wait<0>();
    if (elect && !second) mbar_arrive(bar_out);
    if (elect) TL(24 + second);
    send(IC<0>{}, second ? base + OFF_B + B_BYTES : base + 3 * A_BYTES, A_BYTES / 2);
    cut(64);
    mbar_wait(full0 + 24, 1);
    if (second) mbar_wait(full0, 0);
    named_bar(5 + second, 256);
    stamp(KT - 2);
    turn(IC<64>{}, 0, 1);
    turn(IC<64>{}, A_BYTES, 6);
    turn(IC<64>{}, 2 * A_BYTES, 7);
    if (!second) mbar_wait(full0, 0);
    turn(IC<64>{}, a3, 0);
    if (!second) named_arrive(6, 256);
    stamp(KT - 1);
    wgmma_wait<2>();
    named_bar(2 + wg, 128);
    wgmma_wait<0>();
    if (elect) TL(20 + second);
    send(IC<64>{}, a_base, A_BYTES);
    if (wi == 0) {
      bulk_commit();
      bulk_wait_read<0>();
      if (second && elect) TL(18);
    }
  }
}

typedef CUresult (*EncodeFn)(CUtensorMap*, CUtensorMapDataType, cuuint32_t, void*, const cuuint64_t*, const cuuint64_t*, const cuuint32_t*,
                             const cuuint32_t*, CUtensorMapInterleave, CUtensorMapSwizzle, CUtensorMapL2promotion, CUtensorMapFloatOOBfill);

void make_map(EncodeFn enc, CUtensorMap* m, void* ptr, uint64_t rows, uint64_t cols, uint32_t box_rows, CUtensorMapL2promotion promo,
              uint32_t box_cols = 64, CUtensorMapSwizzle sw = CU_TENSOR_MAP_SWIZZLE_128B) {
  cuuint64_t dims[2] = {cols, rows};
  cuuint64_t strides[1] = {cols * 2};
  cuuint32_t box[2] = {box_cols, box_rows};
  cuuint32_t es[2] = {1, 1};
  enc(m, CU_TENSOR_MAP_DATA_TYPE_BFLOAT16, 2, ptr, dims, strides, box, es, CU_TENSOR_MAP_INTERLEAVE_NONE, sw, promo,
      CU_TENSOR_MAP_FLOAT_OOB_FILL_NONE);
}

void make_map5(EncodeFn enc, CUtensorMap* m, void* ptr, uint64_t cols, uint32_t box_rows, uint32_t box_cols, CUtensorMapSwizzle sw) {
  cuuint64_t dims[5] = {cols, 2, 2, PG, 512 / PG};
  cuuint64_t strides[4] = {cols * 2 * 1024, cols * 2 * 512, cols * 2 * (512 / PG), cols * 2};
  cuuint32_t box[5] = {box_cols, 2, 2, PG, box_rows / (4 * PG)};
  cuuint32_t es[5] = {1, 1, 1, 1, 1};
  enc(m, CU_TENSOR_MAP_DATA_TYPE_BFLOAT16, 5, ptr, dims, strides, box, es, CU_TENSOR_MAP_INTERLEAVE_NONE, sw,
      CU_TENSOR_MAP_L2_PROMOTION_L2_128B, CU_TENSOR_MAP_FLOAT_OOB_FILL_NONE);
}

}

extern "C" void kernel_launch(void* const* d_in, const int* in_sizes, int n_in, void* d_out, int out_size) {
  (void)in_sizes; (void)n_in; (void)out_size;
  void* fn = nullptr;
  cudaDriverEntryPointQueryResult qr;
  cudaGetDriverEntryPoint("cuTensorMapEncodeTiled", &fn, cudaEnableDefault, &qr);
  EncodeFn enc = (EncodeFn)fn;
  void* ab = nullptr;
  cudaGetSymbolAddress(&ab, g_ab);
  Maps maps;
  const CUtensorMapL2promotion P256 = CU_TENSOR_MAP_L2_PROMOTION_L2_256B, P128 = CU_TENSOR_MAP_L2_PROMOTION_L2_128B;
  {
    cuuint64_t dims[3] = {D_, 512, 4}, strides[2] = {D_ * 2, D_ * 2 * 512};
    cuuint32_t box[3] = {64, 64, 2}, es[3] = {1, 1, 1};
    enc(&maps.x, CU_TENSOR_MAP_DATA_TYPE_BFLOAT16, 3, d_in[0], dims, strides, box, es, CU_TENSOR_MAP_INTERLEAVE_NONE,
        CU_TENSOR_MAP_SWIZZLE_128B, P256, CU_TENSOR_MAP_FLOAT_OOB_FILL_NONE);
  }
  for (int p = 0; p < 2; p++) {
    make_map5(enc, &maps.ws[p], d_in[1 + p], S_, 256, 64, CU_TENSOR_MAP_SWIZZLE_128B);
    make_map5(enc, &maps.ws_h[p], d_in[1 + p], S_, 128, 64, CU_TENSOR_MAP_SWIZZLE_128B);
    make_map5(enc, &maps.ws_pf[p], d_in[1 + p], S_, 32, 128, CU_TENSOR_MAP_SWIZZLE_NONE);
  }
  for (int p = 0; p < 2; p++) {
    cuuint64_t dims[3] = {D_, 2, 512}, strides[2] = {D_ * 2 * 512, D_ * 2};
    cuuint32_t box[3] = {64, 2, 64}, es[3] = {1, 1, 1};
    enc(&maps.wd[p], CU_TENSOR_MAP_DATA_TYPE_BFLOAT16, 3, d_in[3 + p], dims, strides, box, es, CU_TENSOR_MAP_INTERLEAVE_NONE,
        CU_TENSOR_MAP_SWIZZLE_128B, P256, CU_TENSOR_MAP_FLOAT_OOB_FILL_NONE);
  }
  make_map(enc, &maps.ab_ld, ab, 2 * D_, S_, 128, P128);
  make_map(enc, &maps.ab_st, ab, 2 * D_, S_, 64, P128);
  make_map5(enc, &maps.out, d_out, D_, 64, 64, CU_TENSOR_MAP_SWIZZLE_128B);
  cudaFuncSetAttribute(fused_kernel, cudaFuncAttributeMaxDynamicSharedMemorySize, SMEM_BYTES);
  fused_kernel<<<NCTA, 384, SMEM_BYTES, cudaStreamPerThread>>>(
      (const __nv_bfloat16*)d_in[0], (const __nv_bfloat16*)d_in[3], (const __nv_bfloat16*)d_in[4], (const __nv_bfloat16*)d_in[6],
      (const __nv_bfloat16*)d_in[7], (const __nv_bfloat16*)d_in[8], maps, (const __nv_bfloat16*)d_in[9], (__nv_bfloat16*)d_out);
}
```

```cpp
#include <cuda_runtime.h>
#include <cuda_bf16.h>
#include <cuda.h>
#include <stdint.h>

#define DEVI __device__ __forceinline__

namespace {

constexpr int S_ = 2048, D_ = 1024, F_ = 3584;
constexpr int STAGES = 4;
constexpr int A_BYTES = 128 * 64 * 2, B_BYTES = 256 * 64 * 2;
constexpr int K1 = 16, K2 = 32, KT = K1 + K2;
constexpr int NCTA = 128;
constexpr int NFFN = 112;
constexpr int CP0 = 2;
constexpr int NST = 3;
constexpr int PG = 4;
constexpr int PR = 64 / PG;
constexpr int NMIR = 4;
constexpr int NB0 = 8;
constexpr int LN_K0 = 4;
constexpr int GU_KF = 15;
constexpr int GU_K1 = 22;
constexpr int GU_K0 = 24;
constexpr int H_K = 30;
constexpr unsigned long long WS_MASK = 0xd8a000ffc0ull;

constexpr uint32_t SM0 = 1024;
constexpr int OFF_B = STAGES * A_BYTES;
constexpr int OFF_AUX = OFF_B + STAGES * B_BYTES;
constexpr int OFF_RING = 0;
constexpr int OFF_XS = OFF_RING + 3 * 8192;
constexpr int OFF_GU = OFF_XS + 4096;
constexpr int OFF_WSUM = OFF_GU;
constexpr int OFF_STAT = OFF_XS + 8192;
constexpr int OFF_RED = OFF_STAT;
constexpr int OFF_FLAGS = OFF_STAT + 1536;
constexpr int OFF_BAR = OFF_STAT + 2048;
constexpr int OFF_MISC = OFF_BAR + 224;
constexpr int AUX_BYTES = OFF_MISC + 32;
constexpr int SMEM_BYTES = OFF_AUX + AUX_BYTES;
static_assert(SMEM_BYTES <= 232448, "smem");

template <int V> struct IC { static constexpr int value = V; };

struct Maps {
  CUtensorMap x, wd[2], ws[2], ws_h[2], ws_pf[2], ab_ld, ab_st, out;
};

__device__ __nv_bfloat16 g_ab[2 * D_ * S_];
__device__ uint2 g_stat[S_];
__device__ uint2 g_wsum[2 * D_];
__device__ uint2 g_cand[NCTA * 3];
__device__ uint2 g_h[F_];
__device__ __align__(128) uint32_t g_abflag[16 * 3 * 32];
__device__ uint32_t g_ctr;
#define TL(i) do {} while (0)
#define TK(r, k) do {} while (0)

#define TKP(r, k) TK(r, k)
#define TKC(k)
DEVI uint32_t smem_u32(const void* p) { return (uint32_t)__cvta_generic_to_shared(p); }
DEVI void mbar_init(uint32_t bar, uint32_t cnt) { asm volatile("mbarrier.init.shared::cta.b64 [%0], %1;" ::"r"(bar), "r"(cnt) : "memory"); }
DEVI void mbar_expect_tx(uint32_t bar, uint32_t bytes) { asm volatile("mbarrier.arrive.expect_tx.shared::cta.b64 _, [%0], %1;" ::"r"(bar), "r"(bytes) : "memory"); }
DEVI void mbar_arrive(uint32_t bar) { asm volatile("mbarrier.arrive.shared::cta.b64 _, [%0];" ::"r"(bar) : "memory"); }
DEVI void mbar_arrive_cluster(uint32_t bar, uint32_t cta) {
  asm volatile("{\n.reg .b32 ra;\nmapa.shared::cluster.u32 ra, %0, %1;\nmbarrier.arrive.shared::cluster.b64 _, [ra];\n}" ::"r"(bar), "r"(cta) : "memory");
}
DEVI uint32_t mapa(uint32_t a, uint32_t cta) { uint32_t r; asm("mapa.shared::cluster.u32 %0, %1, %2;" : "=r"(r) : "r"(a), "r"(cta)); return r; }
DEVI void st_async4(uint32_t dst, float a, float b, float c, float d, uint32_t bar) {
  asm volatile("st.async.shared::cluster.mbarrier::complete_tx::bytes.v4.f32 [%0], {%1, %2, %3, %4}, [%5];"
               ::"r"(dst), "f"(a), "f"(b), "f"(c), "f"(d), "r"(bar) : "memory");
}
DEVI bool mbar_try_wait(uint32_t bar, uint32_t parity) {
  uint32_t ok;
  asm volatile("{\n.reg .pred p;\nmbarrier.try_wait.parity.shared::cta.b64 p, [%1], %2;\nselp.u32 %0, 1, 0, p;\n}" : "=r"(ok) : "r"(bar), "r"(parity) : "memory");
  return ok;
}
DEVI bool mbar_test(uint32_t bar, uint32_t parity) {
  uint32_t ok;
  asm volatile("{\n.reg .pred p;\nmbarrier.test_wait.parity.shared::cta.b64 p, [%1], %2;\nselp.u32 %0, 1, 0, p;\n}" : "=r"(ok) : "r"(bar), "r"(parity) : "memory");
  return ok;
}
DEVI void mbar_wait(uint32_t bar, uint32_t parity) {
  uint32_t n = 0;
  while (!mbar_try_wait(bar, parity)) { if (++n > (1u << 20)) __trap(); }
}
DEVI void tma_load(uint32_t dst, const CUtensorMap* m, int c0, int c1, uint32_t bar) {
  asm volatile("cp.async.bulk.tensor.2d.shared::cluster.global.mbarrier::complete_tx::bytes [%0], [%1, {%3, %4}], [%2];"
               ::"r"(dst), "l"(m), "r"(bar), "r"(c0), "r"(c1) : "memory");
}
DEVI void tma_load3(uint32_t dst, const CUtensorMap* m, int c0, int c1, int c2, uint32_t bar) {
  asm volatile("cp.async.bulk.tensor.3d.shared::cluster.global.mbarrier::complete_tx::bytes [%0], [%1, {%3, %5, %4}], [%2];"
               ::"r"(dst), "l"(m), "r"(bar), "r"(c0), "r"(c2), "r"(c1) : "memory");
}
DEVI void tma_load5(uint32_t dst, const CUtensorMap* m, int c0, int c4, uint32_t bar) {
  asm volatile("{\n.reg .b64 pol;\ncreatepolicy.fractional.L2::evict_first.b64 pol, 1.0;\n"
               "cp.async.bulk.tensor.5d.shared::cluster.global.mbarrier::complete_tx::bytes.L2::cache_hint [%0], [%1, {%3, %5, %5, %5, %4}], [%2], pol;\n}"
               ::"r"(dst), "l"(m), "r"(bar), "r"(c0), "r"(c4), "r"(0) : "memory");
}
DEVI void tma_store(const CUtensorMap* m, uint32_t src, int c0, int c1) {
  asm volatile("cp.async.bulk.tensor.2d.global.shared::cta.bulk_group [%0, {%2, %3}], [%1];" ::"l"(m), "r"(src), "r"(c0), "r"(c1) : "memory");
}
DEVI void tma_red_add(const CUtensorMap* m, uint32_t src, int c0, int c1) {
  asm volatile("cp.reduce.async.bulk.tensor.5d.global.shared::cta.add.bulk_group [%0, {%2, %4, %4, %4, %3}], [%1];" ::"l"(m), "r"(src), "r"(c0), "r"(c1), "r"(0) : "memory");
}
DEVI uint4 lds128(uint32_t a) { uint4 v; asm volatile("ld.shared.v4.u32 {%0,%1,%2,%3}, [%4];" : "=r"(v.x), "=r"(v.y), "=r"(v.z), "=r"(v.w) : "r"(a) : "memory"); return v; }
DEVI uint2 lds64(uint32_t a) { uint2 v; asm volatile("ld.shared.v2.u32 {%0,%1}, [%2];" : "=r"(v.x), "=r"(v.y) : "r"(a) : "memory"); return v; }
DEVI uint32_t lds32(uint32_t a) { uint32_t v; asm volatile("ld.volatile.shared.u32 %0, [%1];" : "=r"(v) : "r"(a) : "memory"); return v; }
DEVI void sts32(uint32_t a, uint32_t v) { asm volatile("st.volatile.shared.u32 [%0], %1;" ::"r"(a), "r"(v) : "memory"); }
DEVI void tma_prefetch(const CUtensorMap* m, int c0, int c1) {
  asm volatile("cp.async.bulk.prefetch.tensor.5d.L2.global [%0, {%1, %3, %3, %3, %2}];" ::"l"(m), "r"(c0), "r"(c1), "r"(0) : "memory");
}
DEVI void cp_async16(uint32_t dst, const void* src) { asm volatile("cp.async.cg.shared.global [%0], [%1], 16;" ::"r"(dst), "l"(src) : "memory"); }
DEVI void cp_async16_once(uint32_t dst, const void* src) {
  asm volatile("{\n.reg .b64 pol;\ncreatepolicy.fractional.L2::evict_first.b64 pol, 1.0;\n"
               "cp.async.cg.shared.global.L2::cache_hint [%0], [%1], 16, pol;\n}" ::"r"(dst), "l"(src) : "memory");
}
DEVI bool elect_one() {
  uint32_t p;
  asm volatile("{\n.reg .pred P;\nelect.sync _|P, 0xffffffff;\nselp.u32 %0, 1, 0, P;\n}" : "=r"(p));
  return p;
}
DEVI float sqrt_approx(float v) { float r; asm("sqrt.approx.ftz.f32 %0, %1;" : "=f"(r) : "f"(v)); return r; }
DEVI float rcp_approx(float v) { float r; asm("rcp.approx.ftz.f32 %0, %1;" : "=f"(r) : "f"(v)); return r; }
DEVI void bulk_commit() { asm volatile("cp.async.bulk.commit_group;" ::: "memory"); }
template <int N> DEVI void bulk_wait() { asm volatile("cp.async.bulk.wait_group %0;" ::"n"(N) : "memory"); }
template <int N> DEVI void bulk_wait_read() { asm volatile("cp.async.bulk.wait_group.read %0;" ::"n"(N) : "memory"); }
DEVI void fence_proxy_async() { asm volatile("fence.proxy.async.global;" ::: "memory"); }
DEVI void fence_proxy_async_smem() { asm volatile("fence.proxy.async.shared::cta;" ::: "memory"); }
DEVI void prefetch_map(const CUtensorMap* m) { asm volatile("prefetch.tensormap [%0];" ::"l"(m) : "memory"); }
DEVI void named_bar(int id, int n) { asm volatile("bar.sync %0, %1;" ::"r"(id), "r"(n) : "memory"); }
DEVI void named_arrive(int id, int n) { asm volatile("bar.arrive %0, %1;" ::"r"(id), "r"(n) : "memory"); }
DEVI void wgmma_fence() { asm volatile("wgmma.fence.sync.aligned;" ::: "memory"); }
DEVI void wgmma_commit() { asm volatile("wgmma.commit_group.sync.aligned;" ::: "memory"); }
template <int N> DEVI void wgmma_wait() { asm volatile("wgmma.wait_group.sync.aligned %0;" ::"n"(N) : "memory"); }
DEVI uint64_t make_desc(uint32_t a16) {
  uint64_t d;
  asm("mov.b64 %0, {%1, 0x40000040};" : "=l"(d) : "r"(a16 + 0x10000));
  return d;
}
DEVI uint32_t ld_acquire(const uint32_t* p) { uint32_t v; asm volatile("ld.acquire.gpu.global.u32 %0, [%1];" : "=r"(v) : "l"(p) : "memory"); return v; }
DEVI void fence_gpu() { asm volatile("fence.acq_rel.gpu;" ::: "memory"); }
DEVI uint32_t ld_relaxed(const uint32_t* p) { uint32_t v; asm volatile("ld.relaxed.gpu.global.u32 %0, [%1];" : "=r"(v) : "l"(p) : "memory"); return v; }
DEVI void st_rec(uint2* p, uint32_t a, uint32_t b) {
  asm volatile("{\n.reg .b64 t;\nmov.b64 t, {%1, %2};\nst.relaxed.gpu.global.b64 [%0], t;\n}" ::"l"(p), "r"(a), "r"(b) : "memory");
}
DEVI uint4 ld_rec2(const uint2* p) {
  uint4 v;
  asm volatile("{\n.reg .b64 a, b;\nld.relaxed.gpu.global.v2.b64 {a, b}, [%4];\nmov.b64 {%0, %1}, a;\nmov.b64 {%2, %3}, b;\n}"
               : "=r"(v.x), "=r"(v.y), "=r"(v.z), "=r"(v.w) : "l"(p) : "memory");
  return v;
}
DEVI uint2 ld_rec(const uint2* p) {
  uint2 v;
  asm volatile("{\n.reg .b64 a;\nld.relaxed.gpu.global.b64 a, [%2];\nmov.b64 {%0, %1}, a;\n}" : "=r"(v.x), "=r"(v.y) : "l"(p) : "memory");
  return v;
}
DEVI bool poll_again(bool bad, uint32_t& it) {
  if (!__any_sync(0xffffffffu, bad)) return false;
  if (++it > (1u << 18)) __trap();
  __nanosleep(40);
  return true;
}
DEVI void st_relaxed(uint32_t* p, uint32_t v) { asm volatile("st.relaxed.gpu.global.u32 [%0], %1;" ::"l"(p), "r"(v) : "memory"); }
DEVI uint32_t pack_bf16(float lo, float hi) { uint32_t r; asm("cvt.rn.bf16x2.f32 %0, %1, %2;" : "=r"(r) : "f"(hi), "f"(lo)); return r; }
DEVI float bf_lo(uint32_t v) { return __uint_as_float(v << 16); }
DEVI float bf_hi(uint32_t v) { return __uint_as_float(v & 0xffff0000u); }
DEVI float bf_round(float v) { return bf_hi(pack_bf16(0.f, v)); }
DEVI uint32_t bf2_sub(uint32_t a, uint32_t b) { uint32_t r; asm("sub.rn.bf16x2 %0, %1, %2;" : "=r"(r) : "r"(a), "r"(b)); return r; }
DEVI uint32_t bf2_fma(uint32_t a, uint32_t b, uint32_t c) { uint32_t r; asm("fma.rn.bf16x2 %0, %1, %2, %3;" : "=r"(r) : "r"(a), "r"(b), "r"(c)); return r; }
DEVI void prefetch_l2(const void* p, uint32_t bytes) { asm volatile("cp.async.bulk.prefetch.L2.global [%0], %1;" ::"l"(p), "r"(bytes) : "memory"); }
DEVI void stmatrix_x4_t(uint32_t addr, uint32_t a, uint32_t b, uint32_t c, uint32_t d) {
  asm volatile("stmatrix.sync.aligned.m8n8.x4.trans.shared.b16 [%0], {%1,%2,%3,%4};" ::"r"(addr), "r"(a), "r"(b), "r"(c), "r"(d) : "memory");
}
DEVI void gemv8(float (&acc)[16], const uint4& v, const float2 xv) {
  const uint32_t g4[4] = {v.x, v.y, v.z, v.w};
#pragma unroll
  for (int c = 0; c < 4; c++) {
    const float lo = bf_lo(g4[c]), hi = bf_hi(g4[c]);
    acc[4 * c + 0] = fmaf(lo, xv.x, acc[4 * c + 0]);
    acc[4 * c + 1] = fmaf(lo, xv.y, acc[4 * c + 1]);
    acc[4 * c + 2] = fmaf(hi, xv.x, acc[4 * c + 2]);
    acc[4 * c + 3] = fmaf(hi, xv.y, acc[4 * c + 3]);
  }
}
template <int H, int MASK, int N> DEVI void xreduce(float (&s)[N], int lane) {
  const bool up = lane & MASK;
#pragma unroll
  for (int i = 0; i < H; i++) {
    const float keep = up ? s[i + H] : s[i], send = up ? s[i] : s[i + H];
    s[i] = keep + __shfl_xor_sync(0xffffffffu, send, MASK);
  }
}
DEVI float warp_sum(float v) {
#pragma unroll
  for (int o = 16; o; o >>= 1) v += __shfl_xor_sync(0xffffffffu, v, o);
  return v;
}

#define ACC128 \
      "{%0,%1,%2,%3,%4,%5,%6,%7,%8,%9,%10,%11,%12,%13,%14,%15,%16,%17,%18,%19,%20,%21,%22,%23,%24,%25,%26,%27,%28,%29,%30,%31," \
      "%32,%33,%34,%35,%36,%37,%38,%39,%40,%41,%42,%43,%44,%45,%46,%47,%48,%49,%50,%51,%52,%53,%54,%55,%56,%57,%58,%59,%60,%61,%62,%63," \
      "%64,%65,%66,%67,%68,%69,%70,%71,%72,%73,%74,%75,%76,%77,%78,%79,%80,%81,%82,%83,%84,%85,%86,%87,%88,%89,%90,%91,%92,%93,%94,%95," \
      "%96,%97,%98,%99,%100,%101,%102,%103,%104,%105,%106,%107,%108,%109,%110,%111,%112,%113,%114,%115,%116,%117,%118,%119,%120,%121,%122,%123,%124,%125,%126,%127},"
#define R128(d) R8(d, 0), R8(d, 8), R8(d, 16), R8(d, 24), R8(d, 32), R8(d, 40), R8(d, 48), R8(d, 56), R8(d, 64), R8(d, 72), R8(d, 80), \
                R8(d, 88), R8(d, 96), R8(d, 104), R8(d, 112), R8(d, 120)
#define R8(d, i) "+f"(d[i]), "+f"(d[i + 1]), "+f"(d[i + 2]), "+f"(d[i + 3]), "+f"(d[i + 4]), "+f"(d[i + 5]), "+f"(d[i + 6]), "+f"(d[i + 7])
DEVI void wgmma_n256(float (&d)[128], uint64_t da, uint64_t db, int scale_d) {
  asm volatile("{\n.reg .pred p;\nsetp.ne.b32 p, %130, 0;\nwgmma.mma_async.sync.aligned.m64n256k16.f32.bf16.bf16 " ACC128
               " %128, %129, p, 1, 1, 0, 0;\n}\n" : R128(d) : "l"(da), "l"(db), "r"(scale_d));
}
DEVI void wgmma_n256_rs(float (&d)[128], uint32_t a0, uint32_t a1, uint32_t a2, uint32_t a3, uint64_t db) {
  asm volatile("wgmma.mma_async.sync.aligned.m64n256k16.f32.bf16.bf16 " ACC128 " {%128, %129, %130, %131}, %132, 1, 1, 1, 0;\n"
               : R128(d) : "r"(a0), "r"(a1), "r"(a2), "r"(a3), "l"(db));
}

#define ACC64 \
      "{%0,%1,%2,%3,%4,%5,%6,%7,%8,%9,%10,%11,%12,%13,%14,%15,%16,%17,%18,%19,%20,%21,%22,%23,%24,%25,%26,%27,%28,%29,%30,%31," \
      "%32,%33,%34,%35,%36,%37,%38,%39,%40,%41,%42,%43,%44,%45,%46,%47,%48,%49,%50,%51,%52,%53,%54,%55,%56,%57,%58,%59,%60,%61,%62,%63},"
template <int O> DEVI void wgmma_n128(float (&d)[128], uint64_t da, uint64_t db) {
  asm volatile("wgmma.mma_async.sync.aligned.m64n128k16.f32.bf16.bf16 " ACC64 " %64, %65, 1, 1, 1, 0, 0;\n"
               : R8(d, O), R8(d, O + 8), R8(d, O + 16), R8(d, O + 24), R8(d, O + 32), R8(d, O + 40), R8(d, O + 48), R8(d, O + 56)
               : "l"(da), "l"(db));
}

DEVI void wait_out_init(uint32_t tag) {
  uint32_t it = 0;
  while ((int32_t)(ld_acquire(&g_ctr) - tag) < 0) { if (++it > (1u << 20)) __trap(); }
}
template <int N> DEVI void cp_wait() { asm volatile("cp.async.wait_group %0;" ::"n"(N) : "memory"); }

DEVI int other_chunk(int m, int j) { return m + (m >= j); }
DEVI int p2_col(int n, int j) {
  const int m = n < 18 ? n - 11 : (n - 18) >> 1;
  const int slab = n < 18 ? 1 : 2 + (n & 1);
  return other_chunk(m, j) * 256 + slab * 64;
}

__global__ void __cluster_dims__(2, 1, 1) __launch_bounds__(384, 1)
fused_kernel(const __nv_bfloat16* __restrict__ x, const __nv_bfloat16* __restrict__ wd_re, const __nv_bfloat16* __restrict__ wd_im,
             const __nv_bfloat16* __restrict__ w_r, const __nv_bfloat16* __restrict__ w_gate, const __nv_bfloat16* __restrict__ w_up,
             const __grid_constant__ Maps maps, const __nv_bfloat16* __restrict__ w_down, __nv_bfloat16* __restrict__ out) {
  extern __shared__ __align__(1024) uint8_t smem[];
  const uint32_t rank = blockIdx.x & 1;
  const uint32_t base = smem_u32(smem);
  uint8_t* aux = smem + OFF_AUX;
  const uint32_t auxs = base + OFF_AUX;
  const uint32_t full0 = auxs + OFF_BAR, empty0 = full0 + 8 * STAGES, bar_stat = empty0 + 8 * STAGES, bar_ab = bar_stat + 8,
                 bar_out = bar_ab + 32, bar_pub = bar_out + 64, bar_gu = bar_pub + 16;
  const uint32_t kcur = auxs + OFF_MISC + 16;

  const int tid = threadIdx.x, lane = tid & 31;
  if (tid == 256) TL(0);
  const int cl = blockIdx.x >> 1;
  const int pos = cl - 4 + max(((cl - 29) * 37) >> 8, 0) + ((cl - 4) >> 31 & (7 * cl + 36));
  const int j = (~pos & 3) * 2 + (pos >> 5), half = (pos >> 2) & 1, eb = (((pos >> 3) + (pos >> 5)) & 3) * 2 + rank;
  {
    const uint32_t dst = base + (tid >> 3) * 128 + (((tid ^ (tid >> 3)) & 7) << 4);
    const char* pa = (const char*)x + (uint32_t)((half * 1024 + j * 64 + (tid >> 3)) * (D_ * 2) + (tid & 7) * 16);
    const uint32_t off = (eb * 64 + (tid >> 4) + (tid & 8) * 64) * (D_ * 2) + (tid & 7) * 16;
    if (tid < 256) {
#pragma unroll
      for (int q = 0; q < 12; q++)
        cp_async16(dst + (q < 4 ? q * 4096 : OFF_B + (q - 4) * 4096),
                   q < 4 ? pa + ((q & 1) * 32 + (q >> 1) * 512) * (D_ * 2) : (const char*)(q < 8 ? wd_re : wd_im) + off + (q & 3) * (16 * D_ * 2));
      asm volatile("cp.async.commit_group;" ::: "memory");
    }
    if (tid == 0) TL(15);
  }
  const int warp = __shfl_sync(0xffffffffu, tid >> 5, 0);
  const int bid = j * 16 + half * 8 + eb;
  const __nv_bfloat16* wd_rows = (bid < 64 ? wd_re : wd_im) + (size_t)(bid & 63) * 16 * D_;
  if (warp == 9) ((uint4*)(aux + OFF_FLAGS))[lane] = make_uint4(0, 0, 0, 0);
  if (tid == 256) {
    prefetch_map(&maps.x);
    prefetch_map(&maps.wd[0]);
    prefetch_map(&maps.wd[1]);
    if (base != (rank << 24) + SM0) __trap();
#pragma unroll
    for (int s = 0; s < STAGES; s++) { mbar_init(full0 + 8 * s, 1); mbar_init(empty0 + 8 * s, 2); }
    mbar_init(bar_stat, 3);
#pragma unroll
    for (int s = 0; s < 4; s++) mbar_init(bar_ab + 8 * s, 4);
    mbar_init(bar_pub, 1);
    mbar_init(bar_pub + 8, 2);
    mbar_init(bar_gu, 1);
    mbar_init(bar_pub + 24, 1);
    sts32(kcur, 0);
    mbar_init(bar_out, 1);
    mbar_init(bar_out + 8, 1);
    asm volatile("fence.mbarrier_init.release.cluster;" ::: "memory");
  }
  __syncthreads();
  asm volatile("barrier.cluster.arrive.relaxed.aligned;" ::: "memory");
  asm volatile("barrier.cluster.wait.acquire.aligned;" ::: "memory");

  if (warp == 8) {
    if (elect_one()) {
      const int arow = eb * 128;
      int pf_i = 0;
      auto prefetch_ws = [&](int k) {
        if ((WS_MASK >> k) & 1) {
          const int q = pf_i < 4 ? pf_i : pf_i < 10 ? pf_i >= 7 : 2 + (pf_i & 1);
          const int c = pf_i < 4 ? j >> 1 : other_chunk(pf_i < 7 ? pf_i - 4 : pf_i < 10 ? pf_i - 7 : (pf_i - 10) >> 1, j >> 1);
          tma_prefetch(&maps.ws_pf[q & 1], half * 1024 + (q & 2) * 256 + c * 128, (j * 8 + eb) * (PR / 8));
          pf_i++;
        }
      };
      auto ws_col = [&](int col) { return half * 1024 + (col & 128) * 4 + (col >> 8) * 64; };
      auto load_b = [&](int st, int col) { tma_load5(base + OFF_B + st * B_BYTES, &maps.ws[(col >> 6) & 1], ws_col(col), j * PR, full0 + 8 * st); };
      TL(1);
#pragma unroll 1
      for (int k = CP0; k < K1 + 2; k++) {
        const int st = k & 3;
        mbar_wait(empty0 + 8 * st, ((k >> 2) & 1) ^ 1);
        TKP(2, k);
        if (k < K1) {
          mbar_expect_tx(full0 + 8 * st, A_BYTES + B_BYTES);
          tma_load3(base + st * A_BYTES, &maps.x, k * 64, j * 64, half * 2, full0 + 8 * st);
          tma_load3(base + OFF_B + st * B_BYTES, &maps.wd[0], k * 64, 0, eb * 64, full0 + 8 * st);
          tma_load3(base + OFF_B + st * B_BYTES + B_BYTES / 2, &maps.wd[1], k * 64, 0, eb * 64, full0 + 8 * st);
        } else {
          mbar_expect_tx(full0 + 8 * st, B_BYTES);
          load_b(st, j * 256 + (k - K1) * 64);
        }
        sts32(kcur, k);
        if (k == 4) { prefetch_l2(wd_rows, 16 * D_ * 2); prefetch_map(&maps.ws[0]); prefetch_map(&maps.ws[1]); prefetch_map(&maps.ws_pf[0]); prefetch_map(&maps.ws_pf[1]); prefetch_map(&maps.ab_ld); prefetch_map(&maps.ab_st); }
        prefetch_ws(k);
      }
      mbar_wait(bar_stat, 0);
      const uint32_t tag = lds32(auxs + OFF_MISC);
      uint32_t* flags = g_abflag + (eb * 2 + half) * 96;
      auto put = [&](int h) {
        tma_store(&maps.ab_st, base + h * (A_BYTES / 2), j * 256 + (h >> 1) * 64, half * 1024 + arow + (h & 1) * 64);
        bulk_commit();
      };
      auto own_b = [&](int q) {
        mbar_wait(empty0 + 8 * q, 1);
        TKP(2, K1 + q);
        sts32(kcur, K1 + q);
        mbar_expect_tx(full0 + 8 * q, B_BYTES);
        load_b(q, j * 256 + q * 64);
      };
      mbar_wait(bar_ab + 8, 0);
      fence_proxy_async_smem();
      put(0);
      mbar_wait(bar_ab, 0);
      put(1);
      TL(8);
      own_b(2);
      bulk_wait<0>();
      TL(11);
      mbar_arrive(bar_pub + 24);
      own_b(3);
      const uint32_t mirror = auxs + OFF_FLAGS;
      uint32_t mc = 0;
      auto refresh = [&](int lv) {
        cp_async16(mirror + mc + lv * 32, flags + lv * 32);
        cp_async16(mirror + mc + lv * 32 + 16, flags + lv * 32 + 4);
        mc = (mc + 128) & (NMIR * 128 - 1);
      };
      auto ready = [&](int f) {
        uint32_t v[NMIR];
#pragma unroll
        for (int i = 0; i < NMIR; i++) v[i] = lds32(mirror + f * 4 + i * 128);
        bool r = false;
#pragma unroll
        for (int i = 0; i < NMIR; i++) r |= v[i] == tag;
        return r;
      };
      auto level_set = [&](int lv) {
        bool r = false;
#pragma unroll
        for (int i = 0; i < NMIR; i++) {
          const uint4 u = lds128(mirror + i * 128 + lv * 32), v = lds128(mirror + i * 128 + lv * 32 + 16);
          r |= ((u.x ^ tag) | (u.y ^ tag) | (u.z ^ tag) | (u.w ^ tag) | (v.x ^ tag) | (v.y ^ tag) | (v.z ^ tag) | (v.w ^ tag)) == 0;
        }
        return r;
      };
      auto wait_level = [&](int lv) {
        uint32_t it = 0;
        while (!level_set(lv)) {
          refresh(lv);
          if (++it > (1u << 20)) __trap();
          __nanosleep(150);
        }
      };
      auto load_a = [&](int st, uint32_t dst, int col) { tma_load(dst, &maps.ab_ld, col, half * 1024 + arow, full0 + 8 * st); };
      mbar_wait(bar_ab + 16, 0);
      mbar_wait(bar_ab + 24, 0);
      fence_proxy_async_smem();
      refresh(0);
      {
        uint32_t it = 0;
        while (!mbar_test(empty0, 0)) {
          __nanosleep(150);
          refresh(0);
          if (++it > (1u << 20)) __trap();
        }
      }
      uint32_t seen = 0;
      bool ahead = false;
      auto issue_b = [&](int n) {
        TKP(2, K1 + n);
        mbar_expect_tx(full0 + 8 * (n & 3), A_BYTES + B_BYTES);
        load_b(n & 3, other_chunk(n - 4, j) * 256);
      };
      auto try_ahead = [&](int n) {
        if (n < 7 && !ahead && mbar_test(empty0 + 8 * (n - 3), 0)) { issue_b(n + 1); ahead = true; }
      };
#pragma unroll 1
      for (int n = 4; n < 11; n++) {
        const int k = K1 + n, st = k & 3;
        const int c = other_chunk(n - 4, j);
        if (!ahead) {
          mbar_wait(empty0 + 8 * st, ((k >> 2) & 1) ^ 1);
          issue_b(n);
        }
        ahead = false;
        if (n == 4) put(4);
        uint32_t it = 3;
        while (!(seen & 1) && !ready(c)) {
          if ((++it & 3) == 0) refresh(0);
          if (it > (1u << 22)) __trap();
          try_ahead(n);
        }
        if (n == 5) mbar_wait(bar_pub, 0);
        if (n == 6) bulk_wait_read<1>();
        if (n == 7) { bulk_wait<0>(); mbar_arrive(bar_pub + 8); TL(23); }
        TKP(3, k);
        load_a(st, base + st * A_BYTES, c * 256);
        try_ahead(n);
        if (n < 7) put(n + 1);
        sts32(kcur, k);
        seen >>= 1;
        if (n < 9) {
          if (ready(other_chunk(n - 2, j))) seen |= 2;
          else refresh(0);
        }
        if (n == 8) refresh(1);
      }
#pragma unroll 1
      for (int k = K1 + 11; k < KT - 3; k++) {
        const int st = k & 3, col = p2_col(k - K1, j);
        if (k == K1 + 11 || k == K1 + 18) wait_level(k == K1 + 11 ? 1 : 2);
        mbar_wait(empty0 + 8 * st, ((k >> 2) & 1) ^ 1);
        TKP(2, k);
        mbar_expect_tx(full0 + 8 * st, A_BYTES + B_BYTES);
        load_b(st, col);
        load_a(st, base + st * A_BYTES, col);
        sts32(kcur, k);
        if (k == K1 + 15) refresh(2);
        prefetch_ws(k);
        if (k == K1 + 20) { prefetch_map(&maps.ws_h[0]); prefetch_map(&maps.ws_h[1]); prefetch_map(&maps.out); }
      }
      const int c1 = p2_col(K2 - 3, j), c2 = p2_col(K2 - 2, j), c3 = c2 + 64;
      auto load_h = [&](int hs, int col, int h, int st) {
        tma_load5(base + OFF_B + hs * (B_BYTES / 2), &maps.ws_h[(col >> 6) & 1], ws_col(col), j * PR + h * (PR / 2), full0 + 8 * st);
      };
      mbar_wait(empty0 + 8, 0);
      TKP(2, KT - 3);
      mbar_expect_tx(full0 + 8, A_BYTES + B_BYTES);
      load_h(2, c1, 0, 1);
      load_a(1, base + A_BYTES, c1);
      load_a(1, base + OFF_B + 3 * (B_BYTES / 2), c3);
      sts32(kcur, KT - 3);
      wait_out_init(tag);
      mbar_arrive(bar_out + 8);
      mbar_wait(empty0 + 16, 0);
      TKP(2, KT - 2);
      mbar_expect_tx(full0 + 16, A_BYTES + B_BYTES);
      load_h(4, c2, 0, 2);
      load_a(2, base + 2 * A_BYTES, c2);
      load_h(5, c3, 0, 2);
      mbar_wait(empty0 + 24, 0);
      TKP(2, KT - 1);
      mbar_expect_tx(full0 + 24, B_BYTES);
      load_h(6, c1, 1, 3);
      load_h(7, c2, 1, 3);
      mbar_wait(empty0, 1);
      TL(17);
      mbar_expect_tx(full0, B_BYTES / 2);
      load_h(0, c3, 1, 0);
      asm volatile("cp.async.wait_all;" ::: "memory");
    }
  } else if (warp > 8) {
    const int t = tid - 288, w = warp - 9;
    float2* xs = (float2*)(aux + OFF_XS);
    float* red = (float*)(aux + OFF_RED);
    volatile uint32_t* misc = (volatile uint32_t*)(aux + OFF_MISC);

    const uint32_t ring = auxs + OFF_RING + (t >> 5) * 8192 + lane * 16;
    auto fetch_to = [&](uint32_t dst, const __nv_bfloat16* src, auto stepc, bool on) {
      if (on) {
#pragma unroll
        for (int k = 0; k < 4; k++) {
          if (decltype(stepc)::value == 256) cp_async16(dst + k * 512, src + k * 256);
          else cp_async16_once(dst + k * 512, src + k * decltype(stepc)::value);
        }
      }
      asm volatile("cp.async.commit_group;" ::: "memory");
    };
    auto fetch = [&](int slot, const __nv_bfloat16* src, auto stepc, bool on) { fetch_to(ring + slot * 2048, src, stepc, on); };
    const int nrow = w ? 5 : 6, lrow0 = w ? 1 + 5 * w : 0;
    const int row0 = bid * 16 + lrow0;
    const __nv_bfloat16* xrow = x + (size_t)row0 * D_ + lane * 8;
    const __nv_bfloat16* wrow = wd_rows + lrow0 * D_ + lane * 8;
    const int slot4 = (OFF_XS - OFF_RING) / 2048 - 4 * w + (w ? w - 1 : 2);
    auto pace = [&](int k) {
      uint32_t it = 0;
      while ((int)lds32(kcur) < k) {
        if (++it > (1u << 20)) __trap();
        __nanosleep(50);
      }
    };
    auto fetch_row = [&](const __nv_bfloat16* p, int i) { fetch(i < 4 ? i : slot4 + i - 4, p + i * D_, IC<256>{}, i < nrow); };
    auto load_row = [&](int i, uint32_t (&xv)[16]) {
      const uint32_t a = ring + (i < 4 ? i : slot4 + i - 4) * 2048;
#pragma unroll
      for (int k = 0; k < 4; k++) {
        const uint4 v = lds128(a + k * 512);
        xv[4 * k] = v.x; xv[4 * k + 1] = v.y; xv[4 * k + 2] = v.z; xv[4 * k + 3] = v.w;
      }
    };
    mbar_wait(full0, 0);
    if (w == 0) asm volatile("prefetch.global.L2 [%0];" ::"l"(wd_rows + (lane >> 1) * D_ + (4 + (lane & 1)) * 64) : "memory");
#pragma unroll
    for (int i = 0; i < 3; i++) fetch_row(xrow, i);
    const uint32_t tag = (ld_relaxed(&g_ctr) & ~(uint32_t)(NCTA - 1)) + NCTA;
    const uint32_t tag16 = (tag >> 7) & 0xffffu, tag5 = (tag16 & 31u) << 11;
    uint32_t xo[6][16];
    auto store_row = [&](int i) {
#pragma unroll
      for (int k = 0; k < 4; k++)
        *(uint4*)(out + (size_t)(row0 + i) * D_ + lane * 8 + k * 256) = make_uint4(xo[i][4 * k], xo[i][4 * k + 1], xo[i][4 * k + 2], xo[i][4 * k + 3]);
    };
    {
      uint4 wv4[4];
#pragma unroll
      for (int k = 0; k < 4; k++) wv4[k] = __ldg((const uint4*)(w_r + lane * 8 + k * 256));
      float sh[8];
      const int ri = nrow - 1 - (lane & 7);
      float wr[32];
      float wrsum = 0.f;
#pragma unroll
      for (int k = 0; k < 4; k++) {
        const uint32_t wv[4] = {wv4[k].x, wv4[k].y, wv4[k].z, wv4[k].w};
#pragma unroll
        for (int c = 0; c < 4; c++) {
          wr[8 * k + 2 * c] = bf_lo(wv[c]);
          wr[8 * k + 2 * c + 1] = bf_hi(wv[c]);
          wrsum += wr[8 * k + 2 * c] + wr[8 * k + 2 * c + 1];
        }
      }
      wrsum = warp_sum(wrsum);
#pragma unroll
      for (int q = 0; q < 8; q++) sh[q] = 0.f;
#pragma unroll 1
      for (int i = 0; i < nrow; i++) {
        uint32_t xv[16];
        if (i + 3 < nrow) pace(LN_K0 + i);
        fetch_row(xrow, i + 3);
        cp_wait<3>();
        load_row(i, xv);
        float s0 = 0.f, s1 = 0.f, q0 = 0.f, q1 = 0.f, r0 = 0.f, r1 = 0.f;
#pragma unroll
        for (int c = 0; c < 16; c++) {
          const float a = bf_lo(xv[c]), b = bf_hi(xv[c]);
          s0 += a;
          s1 += b;
          q0 = fmaf(a, a, q0);
          q1 = fmaf(b, b, q1);
          r0 = fmaf(a, wr[2 * c], r0);
          r1 = fmaf(b, wr[2 * c + 1], r1);
        }
        float s[4] = {s0 + s1, q0 + q1, r0 + r1, 0.f};
        xreduce<2, 16>(s, lane);
        xreduce<1, 8>(s, lane);
#pragma unroll
        for (int q = 5; q > 0; q--) sh[q] = sh[q - 1];
        sh[0] = s[0];
      }
#pragma unroll
      for (int i = 0; i < 6; i++) load_row(min(i, nrow - 1), xo[i]);
#pragma unroll
      for (int i = 0; i < 6; i++) fetch_row(wrow, i);
      xreduce<4, 4>(sh, lane);
      xreduce<2, 2>(sh, lane);
      xreduce<1, 1>(sh, lane);
      const float mean = __shfl_sync(0xffffffffu, sh[0], lane & 7) * (1.f / D_);
      float var = fmaf(-mean, mean, __shfl_sync(0xffffffffu, sh[0], 8 + (lane & 7)) * (1.f / D_));
      const float dot = __shfl_sync(0xffffffffu, sh[0], 16 + (lane & 7));
      if (__any_sync(0xffffffffu, mean * mean > 16.f * var)) {
#pragma unroll 1
        for (int i = 0; i < nrow; i++) {
          const uint32_t* xv = (const uint32_t*)(x + (size_t)(row0 + i) * D_) + lane;
          const float m = __shfl_sync(0xffffffffu, mean, nrow - 1 - i);
          float qq = 0.f;
#pragma unroll 4
          for (int c = 0; c < 16; c++) {
            const uint32_t v = __ldg(xv + 32 * c);
            const float a = bf_lo(v) - m, b = bf_hi(v) - m;
            qq = fmaf(a, a, fmaf(b, b, qq));
          }
          qq = warp_sum(qq) * (1.f / D_);
          if (ri == i) var = qq;
        }
      }
      const float mb = bf_round(mean);
      const float den = bf_round(sqrt_approx(bf_round(bf_round(var) + 1e-5f)));
      const float inv = rcp_approx(den);
      if (lane < nrow) st_rec(g_stat + row0 + ri, __float_as_uint(inv), __float_as_uint(mb) | tag16);
      const uint32_t u = pack_bf16(0.f, fmaf(-mb, wrsum, dot) * inv);
      const uint32_t key = lane < nrow ? ((u ^ (0x80000000u | (uint32_t)((int32_t)u >> 31))) & 0xffff0000u) | tag5 | (uint32_t)(S_ - 1 - row0 - ri) : 0u;
      const uint32_t k0 = __reduce_max_sync(0xffffffffu, key);
      const uint32_t k1 = __reduce_max_sync(0xffffffffu, key == k0 ? 0u : key);
      if (lane == 0) { st_rec(g_cand + bid * 3 + w, k0, k1); TL(26 + w); }
      const uint32_t mi = pack_bf16(mb, inv);
      auto out_rows = [&](int lo, int hi) {
#pragma unroll
        for (int i = lo; i < hi; i++) {
          const uint32_t mv = __shfl_sync(0xffffffffu, mi, nrow - 1 - i);
          const uint32_t mb2 = __byte_perm(mv, 0, 0x1010), inv2 = __byte_perm(mv, 0, 0x3232);
#pragma unroll
          for (int c = 0; c < 16; c++) xo[i][c] = bf2_fma(bf2_sub(xo[i][c], mb2), inv2, xo[i][c]);
          if (i < NST) store_row(i);
        }
      };
      out_rows(0, NST);
      if (t == 0) TL(16);
#pragma unroll
      for (int q = 0; q < 8; q++) sh[q] = 0.f;
#pragma unroll 1
      for (int i0 = 0; i0 < 6; i0 += 2) {
        uint32_t xv[2][16];
        cp_wait<4>();
        asm volatile("cp.async.commit_group;\ncp.async.commit_group;" ::: "memory");
        load_row(i0, xv[0]);
        load_row(min(i0 + 1, nrow - 1), xv[1]);
        float s0 = 0.f, s1 = 0.f, s2 = 0.f, s3 = 0.f;
#pragma unroll
        for (int c = 0; c < 16; c++) { s0 += bf_lo(xv[0][c]); s1 += bf_hi(xv[0][c]); s2 += bf_lo(xv[1][c]); s3 += bf_hi(xv[1][c]); }
#pragma unroll
        for (int q = 5; q > 1; q--) sh[q] = sh[q - 2];
        sh[1] = s0 + s1;
        sh[0] = s2 + s3;
      }
      xreduce<4, 4>(sh, lane);
      xreduce<2, 2>(sh, lane);
      xreduce<1, 1>(sh, lane);
      sh[0] += __shfl_xor_sync(0xffffffffu, sh[0], 8);
      sh[0] += __shfl_xor_sync(0xffffffffu, sh[0], 16);
      const float wv = -sh[0], hi = bf_hi(__float_as_uint(wv)), mid = bf_hi(__float_as_uint(wv - hi));
      if (lane < 6 && 5 - lane < nrow)
        st_rec(g_wsum + row0 + 5 - lane, __byte_perm(__float_as_uint(hi), __float_as_uint(mid), 0x7632), __byte_perm(__float_as_uint(wv - hi - mid), tag16, 0x5432));
      if (t == 0) TL(7);
      out_rows(NST, 6);
    }
    const int nblk = bid < NFFN ? (w ? (32 - NB0) / 2 : NB0) : 0, blk0 = w ? NB0 + (w - 1) * ((32 - NB0) / 2) : 0;
    if (t == 0) TL(2);
    const size_t guoff = (size_t)(rank * 512 + 16 * blk0 + (lane >> 3)) * F_ + (bid >> 1) * 64 + (lane & 7) * 8;
    const __nv_bfloat16 *pg = w_gate + guoff, *pu = w_up + guoff;
    auto fill = [&]() {
      pace(GU_KF);
      fetch(0, pg, IC<4 * F_>{}, nblk);
      fetch(1, pu, IC<4 * F_>{}, nblk);
      fetch(2, pg + 16 * F_, IC<4 * F_>{}, nblk);
      fetch(3, pu + 16 * F_, IC<4 * F_>{}, nblk);
#pragma unroll
      for (int i = NST; i < 5; i++) store_row(i);
      if (w == 0) store_row(5);
    };
    if (w == 0) {
      uint2 ws[8];
      uint32_t it = 0, bad;
      auto load_ws = [&]() {
#pragma unroll
        for (int i = 0; i < 8; i++) ws[i] = ld_rec(g_wsum + eb * 64 + (lane >> 1) + (lane & 1) * 512 + (i & 3) * 16 + (i >> 2) * 1024);
      };
      load_ws();
      if (lane == 0) misc[0] = tag;
      while (true) {
        bad = 0;
#pragma unroll
        for (int i = 0; i < 8; i++) bad |= (ws[i].y >> 16) ^ tag16;
        if (!poll_again(bad, it)) break;
        load_ws();
      }
#pragma unroll
      for (int i = 0; i < 8; i++) ((uint4*)(aux + OFF_WSUM))[32 * i + lane] = make_uint4(ws[i].x, ws[i].y & 0xffffu, 0u, 0u);
      fence_proxy_async_smem();
      __syncwarp();
      if (lane == 0) { mbar_arrive(bar_stat); TL(3); }
      fill();
    } else {
      uint4 kv[6], cs;
      uint32_t it = 0, bad;
      do {
        cs = ld_rec2(g_stat + half * 1024 + (w - 1) * 512 + j * 64 + 2 * lane);
        bad = ((cs.y ^ tag16) | (cs.w ^ tag16)) & 0xffffu ? 0xf800u : 0u;
#pragma unroll
        for (int i = 0; i < 6; i++) kv[i] = ld_rec2(g_cand + 2 * lane + 64 * i);
#pragma unroll
        for (int i = 0; i < 6; i++) bad |= (kv[i].x ^ tag5) | (kv[i].z ^ tag5);
      } while (poll_again(bad & 0xf800u, it));
      ((uint4*)(aux + OFF_STAT))[t - 32] = make_uint4(cs.x, __byte_perm(cs.y, 0, 0x3232), cs.z, __byte_perm(cs.w, 0, 0x3232));
      __syncwarp();
      if (lane == 0) mbar_arrive(bar_stat);
      uint32_t k0 = 0, k1 = 0;
#pragma unroll
      for (int i = 0; i < 6; i++) {
        const uint32_t c0 = max(kv[i].x, kv[i].z), c1 = max(min(kv[i].x, kv[i].z), max(kv[i].y, kv[i].w));
        k1 = max(max(k1, c1), min(k0, c0));
        k0 = max(k0, c0);
      }
      const uint32_t m0 = __reduce_max_sync(0xffffffffu, k0);
      const uint32_t m1 = __reduce_max_sync(0xffffffffu, k0 == m0 ? k1 : k0);
      if (t == 32) { misc[2] = m0; misc[3] = m1; }
      {
        const int r0 = S_ - 1 - (m0 & (S_ - 1)), r1 = S_ - 1 - (m1 & (S_ - 1));
        const uint32_t* pa = (const uint32_t*)(x + (size_t)r0 * D_ + rank * 512 + (w - 1) * 256) + lane;
        const uint32_t* pb = (const uint32_t*)(x + (size_t)r1 * D_ + rank * 512 + (w - 1) * 256) + lane;
        uint32_t xa[4], xb[4];
#pragma unroll
        for (int k = 0; k < 4; k++) { xa[k] = ld_relaxed(pa + 32 * k); xb[k] = ld_relaxed(pb + 32 * k); }
        uint2 sa = ld_rec(g_stat + r0), sb = ld_rec(g_stat + r1);
        fill();
        while (poll_again(((sa.y ^ tag16) | (sb.y ^ tag16)) & 0xffffu, it)) {
          sa = ld_rec(g_stat + r0);
          sb = ld_rec(g_stat + r1);
        }
        const uint32_t ma = __byte_perm(sa.y, 0, 0x3232), mb = __byte_perm(sb.y, 0, 0x3232);
        const float ia = __uint_as_float(sa.x), ib = __uint_as_float(sb.x);
#pragma unroll
        for (int k = 0; k < 4; k++) {
          const uint32_t da = bf2_sub(xa[k], ma), db = bf2_sub(xb[k], mb);
          const uint32_t na = pack_bf16(bf_lo(da) * ia, bf_hi(da) * ia), nb = pack_bf16(bf_lo(db) * ib, bf_hi(db) * ib);
          ((float4*)xs)[(w - 1) * 128 + 32 * k + lane] = make_float4(bf_lo(na), bf_lo(nb), bf_hi(na), bf_hi(nb));
        }
      }
    }
    named_bar(1, 96);
    if (t == 0) TL(4);
    if (t == 32) {
      mbar_wait(bar_ab + 16, 0);
      fence_proxy_async_smem();
      mbar_wait(bar_pub + 24, 0);
      tma_store(&maps.ab_ld, base + A_BYTES, j * 256 + 64, half * 1024 + eb * 128);
      bulk_commit();
      mbar_wait(bar_ab + 24, 0);
      mbar_arrive_cluster(bar_pub + 8, rank ^ 1);
      bulk_wait<0>();
      mbar_arrive(bar_pub);
    }
    if (t == 0) {
      auto flag = [&](int lv) {
        fence_gpu();
        st_relaxed(g_abflag + (eb * 2 + half) * 96 + lv * 32 + j, tag);
      };
      mbar_wait(bar_pub + 24, 0);
      flag(0);
      TL(9);
      mbar_wait(bar_pub, 0);
      flag(1);
      asm volatile("red.relaxed.gpu.global.add.u32 [%0], 1;" ::"l"(&g_ctr) : "memory");
      TL(19);
      mbar_wait(bar_pub + 8, 0);
      flag(2);
      TL(22);
    }
    __syncwarp();
    const int cb = bid & 15, kg = bid >> 4;
    const int ndn = w ? 9 : 10;
    const __nv_bfloat16* pd = w_down + (size_t)(kg * 448 + 16 * w + (lane >> 3)) * D_ + cb * 64 + (lane & 7) * 8;
    uint32_t sa = ring;
    uint4 v0[4], v1[4];
    float2 xv[4] = {};
    auto take = [&](uint4 (&v)[4]) {
      cp_wait<3>();
#pragma unroll
      for (int i = 0; i < 4; i++) v[i] = lds128(sa + i * 512);
    };
    auto next_down = [&](bool on) {
      fetch_to(sa, pd, IC<4 * D_>{}, on);
      pd += 48 * D_;
    };
    auto gemv16 = [&](float (&acc)[16], const uint4 (&v)[4], int h) {
      gemv8(acc, v[2 * h], xv[2 * h]);
      gemv8(acc, v[2 * h + 1], xv[2 * h + 1]);
    };
    if (nblk) {
      float ag[16], au[16];
#pragma unroll
      for (int i = 0; i < 16; i++) { ag[i] = 0.f; au[i] = 0.f; }
      const float2* xp = xs + 16 * blk0 + (lane >> 3);
      int kq = 2 * GU_K1;
      auto refill = [&](int kc, const __nv_bfloat16* p, bool gu) {
        if (kc < (kq >> 1)) pace(kq >> 1);
        kq += kq < 2 * GU_K0 ? 2 : 1;
        if (gu) fetch_to(sa, p, IC<4 * F_>{}, true);
        else next_down(true);
        sa = ring + ((sa - ring + 2048) & 8191);
      };
      take(v0);
      xv[0] = xp[0];
      xv[1] = xp[4];
      pg += 32 * F_;
      pu += 32 * F_;
      refill(0, pg, true);
#pragma unroll 1
      for (int b = 0; b < nblk; b++) {
        take(v1);
        int kc = lds32(kcur);
        xv[2] = xp[8];
        xv[3] = xp[12];
        xp += 16;
        pg += 16 * F_;
        gemv16(ag, v0, 0);
        refill(kc, pu, b + 2 < nblk);
        gemv16(ag, v0, 1);
        take(v0);
        kc = lds32(kcur);
        pu += 16 * F_;
        gemv16(au, v1, 0);
        xv[0] = xp[0];
        xv[1] = xp[4];
        refill(kc, pg, b + 3 < nblk);
        gemv16(au, v1, 1);
      }
      float s[32];
#pragma unroll
      for (int i = 0; i < 16; i++) { s[i] = ag[i]; s[16 + i] = au[i]; }
      xreduce<16, 16>(s, lane);
      xreduce<8, 8>(s, lane);
      mbar_wait(bar_pub + 8, 0);
      const uint32_t dst = mapa(auxs + OFF_GU + (rank * 3 + w) * 512 + (lane >> 4) * 256 + (lane & 3) * 64 + (lane & 8) * 4, (lane >> 2) & 1);
      const uint32_t dbar = mapa(bar_gu, (lane >> 2) & 1);
      st_async4(dst, s[0], s[1], s[2], s[3], dbar);
      st_async4(dst + 16, s[4], s[5], s[6], s[7], dbar);
      if (w == 0) {
        if (lane == 0) mbar_expect_tx(bar_gu, 6 * 512);
        mbar_wait(bar_gu, 0);
        const float2* r2 = (const float2*)(aux + OFF_GU) + lane;
        float2 g2 = r2[0], u2 = r2[32];
#pragma unroll
        for (int q = 1; q < 6; q++) {
          const float2 a = r2[64 * q], c = r2[64 * q + 32];
          g2.x += a.x; g2.y += a.y; u2.x += c.x; u2.y += c.y;
        }
        float hv[2];
#pragma unroll
        for (int tok = 0; tok < 2; tok++) {
          const float g = bf_round(tok ? g2.y : g2.x), u = bf_round(tok ? u2.y : u2.x);
          hv[tok] = bf_round(__fdividef(g, 1.f + __expf(-g))) * u;
        }
        st_rec(g_h + bid * 32 + lane, pack_bf16(hv[0], hv[1]), tag);
        if (lane == 0) TL(5);
      }
    } else {
#pragma unroll
      for (int u = 0; u < 4; u++) fetch(u, pd + u * 48 * D_, IC<4 * D_>{}, true);
      pd += 4 * 48 * D_;
      take(v0);
      next_down(true);
      sa += 2048;
      pace(H_K);
    }
    if (t == 32) wait_out_init(tag);
    named_bar(1, 96);
    {
      uint4 hv[3];
      uint32_t it = 0;
      bool bad[3] = {true, true, w == 0};
      while (true) {
#pragma unroll
        for (int i = 0; i < 3; i++) if (bad[i]) hv[i] = ld_rec2(g_h + kg * 448 + 2 * (t + 96 * i));
#pragma unroll
        for (int i = 0; i < 3; i++) bad[i] = bad[i] && (hv[i].y != tag || hv[i].w != tag);
        if (!poll_again(bad[0] || bad[1] || bad[2], it)) break;
        __nanosleep(100);
      }
#pragma unroll
      for (int i = 0; i < 3; i++) {
        if (t + 96 * i < 224) ((float4*)xs)[t + 96 * i] = make_float4(bf_lo(hv[i].x), bf_hi(hv[i].x), bf_lo(hv[i].z), bf_hi(hv[i].z));
      }
    }
    named_bar(1, 96);
    if (t == 0) TL(10);
    {
      float ay[16];
#pragma unroll
      for (int q = 0; q < 16; q++) ay[q] = 0.f;
      const float2* hp = xs + 16 * w + (lane >> 3);
      xv[0] = hp[0];
      xv[1] = hp[4];
      auto unit = [&](const uint4 (&v)[4], uint4 (&vn)[4], int u) {
        take(vn);
        xv[2] = hp[8];
        xv[3] = hp[12];
        hp += 48;
        gemv16(ay, v, 0);
        xv[0] = hp[0];
        xv[1] = hp[4];
        next_down(u + 5 < ndn);
        sa = ring + ((sa - ring + 2048) & 8191);
        gemv16(ay, v, 1);
      };
#pragma unroll 1
      for (int u = 0; u < ndn; u += 2) {
        unit(v0, v1, u);
        if (u + 1 < ndn) unit(v1, v0, u + 1);
      }
      xreduce<8, 16>(ay, lane);
      xreduce<4, 8>(ay, lane);
      ((float4*)red)[w * 32 + (lane & 7) * 4 + (lane >> 3)] = make_float4(ay[0], ay[1], ay[2], ay[3]);
    }
    named_bar(1, 96);
    if (t < 64) {
      const float* r = red + 4 * lane + w;
      const uint32_t key = misc[2 + w];
      const uint32_t rb = (key ^ (0x80000000u | ~(uint32_t)((int32_t)key >> 31))) & 0xffff0000u;
      const float gate = bf_round(__fdividef(1.f, 1.f + __expf(-__uint_as_float(rb))));
      const uint32_t v = pack_bf16((r[0] + r[128] + r[256]) * gate, (r[2] + r[130] + r[258]) * gate);
      asm volatile("red.relaxed.gpu.global.add.noftz.bf16x2 [%0], %1;"
                   ::"l"(out + (size_t)(S_ - 1 - (key & (S_ - 1))) * D_ + cb * 64 + 2 * lane), "r"(v) : "memory");
      if (t == 0) TL(6);
    }
  } else {
    float acc[128];
    const int wg = warp >> 2, wi = warp & 3;
    const bool elect = (tid & 127) == 0;
    const uint32_t a_base = base + wg * (A_BYTES / 2);

    auto release = [&](int k) {
      if (elect) mbar_arrive(empty0 + 8 * (k & 3));
    };
    const int tw = wg ^ 1;
    auto mma_step = [&](int st, int scale_d, int flip = 0) {
      const uint32_t a = SM0 / 16 + (wg ^ flip) * (A_BYTES / 32) + st * (A_BYTES / 16), b = (SM0 + OFF_B) / 16 + st * (B_BYTES / 16);
      wgmma_fence();
      wgmma_n256(acc, make_desc(a), make_desc(b), scale_d);
      wgmma_n256(acc, make_desc(a + 2), make_desc(b + 2), 1);
      wgmma_n256(acc, make_desc(a + 4), make_desc(b + 4), 1);
      wgmma_commit();
      wgmma_n256(acc, make_desc(a + 6), make_desc(b + 6), 1);
      wgmma_commit();
    };
    auto stamp = [&](int k) {
      if (elect) TK(wg, k);
    };

    {
      const uint32_t dst = (rank << 24) + SM0 + (tid >> 3) * 128 + (((tid ^ (tid >> 3)) & 7) << 4);
      const char* pa = (const char*)x + (uint32_t)((half * 1024 + j * 64 + (tid >> 3)) * (D_ * 2) + (tid & 7) * 16 + 128);
      const uint32_t off = (eb * 64 + (tid >> 4) + (tid & 8) * 64) * (D_ * 2) + (tid & 7) * 16 + 128;
#pragma unroll
      for (int q = 0; q < 12; q++)
        cp_async16(dst + (q < 4 ? A_BYTES + q * 4096 : OFF_B + B_BYTES + (q - 4) * 4096),
                   q < 4 ? pa + ((q & 1) * 32 + (q >> 1) * 512) * (D_ * 2) : (const char*)(q < 8 ? wd_re : wd_im) + off + (q & 3) * (16 * D_ * 2));
      asm volatile("cp.async.commit_group;" ::: "memory");
    }
#pragma unroll 1
    for (int k = 0; k < K1 - 2; k++) {
      if (k < CP0) {
        cp_wait<CP0 - 1>();
        asm volatile("cp.async.commit_group;" ::: "memory");
        fence_proxy_async_smem();
        named_bar(4, 256);
        if (tid == 0) mbar_arrive(full0 + 8 * k);
        stamp(k);
      } else {
        stamp(k);
        mbar_wait(full0 + 8 * (k & 3), (k >> 2) & 1);
        TKC(k);
      }
      mma_step(k & 3, k, 1);
      wgmma_wait<2>();
      if (k) release(k - 1);
    }
    {
      uint2 st0, st1;
      auto stats = [&]() {
        mbar_wait(bar_stat, 0);
        st0 = lds64(auxs + OFF_STAT + (tw * 64 + wi * 16 + (lane >> 2)) * 8);
        st1 = lds64(auxs + OFF_STAT + (tw * 64 + wi * 16 + (lane >> 2)) * 8 + 64);
      };
      mbar_wait(full0 + 16, 1);
      if (tw) {
        wgmma_wait<0>();
        release(K1 - 3);
        mbar_wait(full0 + 24, 1);
        stats();
        named_bar(4, 256);
      }
      stamp(K1 - 2);
      mma_step(2, 1, 1);
      if (!tw) {
        wgmma_wait<2>();
        release(K1 - 3);
        mbar_wait(full0 + 24, 1);
      }
      stamp(K1 - 1);
      mma_step(3, 1, 1);
      if (!tw) stats();
      wgmma_fence();
      wgmma_n256_rs(acc, st0.y, st1.y, 0u, 0u, (uint64_t)((SM0 + OFF_AUX + OFF_WSUM) >> 4) | ((uint64_t)8 << 32));
      wgmma_commit();
      if (!tw) named_bar(4, 256);
      const int r8 = (lane & 1) * 4 + ((lane >> 1) & 3);
      const uint32_t dst = __shfl_sync(0xffffffffu, base + tw * 2 * A_BYTES + ((lane >> 4) * 8 + r8) * 128 + (((2 * wi + ((lane >> 3) & 1)) ^ r8) << 4), lane);
      if (tw) mbar_wait(full0, 0);
      wgmma_wait<3>();
      release(K1 - 2);
      wgmma_wait<1>();
      release(K1 - 1);
      if (tw) mbar_wait(empty0 + 24, 1);
      wgmma_wait<0>();
      if (elect) TL(12 + tw);
#pragma unroll
      for (int p = 0; p < 16; p++) {
        if (p < 8) {
          const float c0 = __uint_as_float(st0.x ^ (p < 4 ? 0 : 0x80000000u)), c1 = __uint_as_float(st1.x ^ (p < 4 ? 0 : 0x80000000u));
#pragma unroll
          for (int i = 16 * p; i < 16 * p + 16; i++) asm volatile("mul.f32 %0, %0, %1;" : "+f"(acc[i]) : "f"(i & 2 ? c1 : c0));
        }
        const float* v = acc + (p & 8) * 8 + (p & 3) * 16 + ((p >> 2) & 1);
        stmatrix_x4_t(dst + p * 2048, pack_bf16(v[0], v[4]), pack_bf16(v[2], v[6]), pack_bf16(v[8], v[12]), pack_bf16(v[10], v[14]));
        if (p == 7 && !tw) {
          mbar_wait(full0, 0);
          fence_proxy_async_smem();
        }
        if (p == 3 || p == 7 || p == 15) {
          __syncwarp();
          if (lane == 0 && (p == 15 || !tw)) mbar_arrive(bar_ab + (p == 3 ? 8 : p == 7 ? 0 : 16 + 8 * tw));
        }
        if (p == 13) {
          mbar_wait(bar_ab, 0);
          mbar_wait(full0 + 8, 0);
        }
      }
      if (elect) TL(29 + tw);
    }
#pragma unroll
    for (int i = 0; i < 128; i++) asm volatile("" : "=f"(acc[i]));
    stamp(K1);
    mma_step(0, 0);
    if (!tw) {
      fence_proxy_async_smem();
      named_bar(2, 128);
    } else {
      mbar_wait(bar_ab + 16, 0);
      fence_proxy_async_smem();
    }
    stamp(K1 + 1);
    mma_step(1, 1);
    wgmma_wait<2>();
    release(K1);
    mbar_wait(bar_ab + 24, 0);
    fence_proxy_async_smem();
#pragma unroll 1
    for (int k = K1 + 2; k < KT - 4; k++) {
      const bool early = k == K1 + 4;
      if (early) {
        wgmma_wait<0>();
        release(k - 1);
      }
      stamp(k);
      mbar_wait(full0 + 8 * (k & 3), (k >> 2) & 1);
      TKC(k);
      mma_step(k & 3, 1);
      wgmma_wait<2>();
      if (!early) release(k - 1);
    }
    const bool second = wg == 0;
    auto turn = [&](auto oc, uint32_t a, int hs) {
      const uint32_t da = (SM0 + a) / 16 + wg * (A_BYTES / 32), db = (SM0 + OFF_B) / 16 + hs * (B_BYTES / 32);
      wgmma_fence();
#pragma unroll
      for (int q = 0; q < 4; q++) wgmma_n128<decltype(oc)::value>(acc, make_desc(da + 2 * q), make_desc(db + 2 * q));
      wgmma_commit();
    };
    constexpr uint32_t a3 = OFF_B + 3 * (B_BYTES / 2);
    const uint32_t o0 = ((lane >> 4) * 8 + (lane & 7)) * 128 + (((2 * wi + ((lane >> 3) & 1)) ^ (lane & 7)) << 4);
    auto send = [&](auto oc, uint32_t dst, uint32_t pitch) {
      constexpr int O = decltype(oc)::value;
#pragma unroll
      for (int h = 0; h < 2; h++) {
#pragma unroll
        for (int p = 0; p < 4; p++) {
          const float* v = acc + O + 32 * h + 8 * p;
          stmatrix_x4_t(dst + h * pitch + o0 + p * 2048, pack_bf16(v[0], v[1]), pack_bf16(v[2], v[3]), pack_bf16(v[4], v[5]), pack_bf16(v[6], v[7]));
        }
        fence_proxy_async_smem();
        named_bar(2 + wg, 128);
        if (wi == 0 && elect_one()) {
          tma_red_add(&maps.out, dst + h * pitch, eb * 64 + wg * 512, (j * 4 + O / 32 + h) * (PR / 4));
          if (h == 0) TL(24 + (O / 32) + second + 9);
        }
        __syncwarp();
      }
    };
    const float one = __uint_as_float(__shfl_sync(0xffffffffu, lds32(kcur) >> 8, 0) | 0x3f800000u);
    auto cut = [&](int lo) {
#pragma unroll
      for (int i = lo; i < lo + 64; i++) acc[i] *= one;
    };
    mbar_wait(full0, 1);
    wgmma_wait<0>();
    release(KT - 5);
    cut(0);
    if (second) {
      mbar_wait(full0 + 8, 1);
      mbar_wait(full0 + 16, 1);
      named_bar(4, 256);
    }
    stamp(KT - 4);
    turn(IC<0>{}, 0, 0);
    if (!second) mbar_wait(full0 + 8, 1);
    turn(IC<0>{}, A_BYTES, 2);
    if (!second) mbar_wait(full0 + 16, 1);
    turn(IC<0>{}, 2 * A_BYTES, 4);
    wgmma_wait<2>();
    release(0);
    turn(IC<0>{}, a3, 5);
    named_arrive(4 + second, 256);
    stamp(KT - 3);
    if (wi == 0) {
      mbar_wait(bar_out + 8, 0);
      fence_proxy_async();
    }
    mbar_wait(second ? bar_out : empty0 + 24, 0);
    wgmma_wait<2>();
    if (second) named_bar(2 + wg, 128);
    wgmma_wait<0>();
    if (elect && !second) mbar_arrive(bar_out);
    if (elect) TL(24 + second);
    send(IC<0>{}, second ? base + OFF_B + B_BYTES : base + 3 * A_BYTES, A_BYTES / 2);
    cut(64);
    mbar_wait(full0 + 24, 1);
    if (second) mbar_wait(full0, 0);
    named_bar(5 + second, 256);
    stamp(KT - 2);
    turn(IC<64>{}, 0, 1);
    turn(IC<64>{}, A_BYTES, 6);
    turn(IC<64>{}, 2 * A_BYTES, 7);
    if (!second) mbar_wait(full0, 0);
    turn(IC<64>{}, a3, 0);
    if (!second) named_arrive(6, 256);
    stamp(KT - 1);
    wgmma_wait<2>();
    named_bar(2 + wg, 128);
    wgmma_wait<0>();
    if (elect) TL(20 + second);
    send(IC<64>{}, a_base, A_BYTES);
    if (wi == 0) {
      bulk_commit();
      bulk_wait_read<0>();
      if (second && elect) TL(18);
    }
  }
}

typedef CUresult (*EncodeFn)(CUtensorMap*, CUtensorMapDataType, cuuint32_t, void*, const cuuint64_t*, const cuuint64_t*, const cuuint32_t*,
                             const cuuint32_t*, CUtensorMapInterleave, CUtensorMapSwizzle, CUtensorMapL2promotion, CUtensorMapFloatOOBfill);

void make_map(EncodeFn enc, CUtensorMap* m, void* ptr, uint64_t rows, uint64_t cols, uint32_t box_rows, CUtensorMapL2promotion promo,
              uint32_t box_cols = 64, CUtensorMapSwizzle sw = CU_TENSOR_MAP_SWIZZLE_128B) {
  cuuint64_t dims[2] = {cols, rows};
  cuuint64_t strides[1] = {cols * 2};
  cuuint32_t box[2] = {box_cols, box_rows};
  cuuint32_t es[2] = {1, 1};
  enc(m, CU_TENSOR_MAP_DATA_TYPE_BFLOAT16, 2, ptr, dims, strides, box, es, CU_TENSOR_MAP_INTERLEAVE_NONE, sw, promo,
      CU_TENSOR_MAP_FLOAT_OOB_FILL_NONE);
}

void make_map5(EncodeFn enc, CUtensorMap* m, void* ptr, uint64_t cols, uint32_t box_rows, uint32_t box_cols, CUtensorMapSwizzle sw) {
  cuuint64_t dims[5] = {cols, 2, 2, PG, 512 / PG};
  cuuint64_t strides[4] = {cols * 2 * 1024, cols * 2 * 512, cols * 2 * (512 / PG), cols * 2};
  cuuint32_t box[5] = {box_cols, 2, 2, PG, box_rows / (4 * PG)};
  cuuint32_t es[5] = {1, 1, 1, 1, 1};
  enc(m, CU_TENSOR_MAP_DATA_TYPE_BFLOAT16, 5, ptr, dims, strides, box, es, CU_TENSOR_MAP_INTERLEAVE_NONE, sw,
      CU_TENSOR_MAP_L2_PROMOTION_L2_128B, CU_TENSOR_MAP_FLOAT_OOB_FILL_NONE);
}

}

extern "C" void kernel_launch(void* const* d_in, const int* in_sizes, int n_in, void* d_out, int out_size) {
  (void)in_sizes; (void)n_in; (void)out_size;
  void* fn = nullptr;
  cudaDriverEntryPointQueryResult qr;
  cudaGetDriverEntryPoint("cuTensorMapEncodeTiled", &fn, cudaEnableDefault, &qr);
  EncodeFn enc = (EncodeFn)fn;
  void* ab = nullptr;
  cudaGetSymbolAddress(&ab, g_ab);
  Maps maps;
  const CUtensorMapL2promotion P256 = CU_TENSOR_MAP_L2_PROMOTION_L2_256B, P128 = CU_TENSOR_MAP_L2_PROMOTION_L2_128B;
  {
    cuuint64_t dims[3] = {D_, 512, 4}, strides[2] = {D_ * 2, D_ * 2 * 512};
    cuuint32_t box[3] = {64, 64, 2}, es[3] = {1, 1, 1};
    enc(&maps.x, CU_TENSOR_MAP_DATA_TYPE_BFLOAT16, 3, d_in[0], dims, strides, box, es, CU_TENSOR_MAP_INTERLEAVE_NONE,
        CU_TENSOR_MAP_SWIZZLE_128B, P256, CU_TENSOR_MAP_FLOAT_OOB_FILL_NONE);
  }
  for (int p = 0; p < 2; p++) {
    make_map5(enc, &maps.ws[p], d_in[1 + p], S_, 256, 64, CU_TENSOR_MAP_SWIZZLE_128B);
    make_map5(enc, &maps.ws_h[p], d_in[1 + p], S_, 128, 64, CU_TENSOR_MAP_SWIZZLE_128B);
    make_map5(enc, &maps.ws_pf[p], d_in[1 + p], S_, 32, 128, CU_TENSOR_MAP_SWIZZLE_NONE);
  }
  for (int p = 0; p < 2; p++) {
    cuuint64_t dims[3] = {D_, 2, 512}, strides[2] = {D_ * 2 * 512, D_ * 2};
    cuuint32_t box[3] = {64, 2, 64}, es[3] = {1, 1, 1};
    enc(&maps.wd[p], CU_TENSOR_MAP_DATA_TYPE_BFLOAT16, 3, d_in[3 + p], dims, strides, box, es, CU_TENSOR_MAP_INTERLEAVE_NONE,
        CU_TENSOR_MAP_SWIZZLE_128B, P256, CU_TENSOR_MAP_FLOAT_OOB_FILL_NONE);
  }
  make_map(enc, &maps.ab_ld, ab, 2 * D_, S_, 128, P128);
  make_map(enc, &maps.ab_st, ab, 2 * D_, S_, 64, P128);
  make_map5(enc, &maps.out, d_out, D_, 64, 64, CU_TENSOR_MAP_SWIZZLE_128B);
  cudaFuncSetAttribute(fused_kernel, cudaFuncAttributeMaxDynamicSharedMemorySize, SMEM_BYTES);
  fused_kernel<<<NCTA, 384, SMEM_BYTES, cudaStreamPerThread>>>(
      (const __nv_bfloat16*)d_in[0], (const __nv_bfloat16*)d_in[3], (const __nv_bfloat16*)d_in[4], (const __nv_bfloat16*)d_in[6],
      (const __nv_bfloat16*)d_in[7], (const __nv_bfloat16*)d_in[8], maps, (const __nv_bfloat16*)d_in[9], (__nv_bfloat16*)d_out);
}
```
